```python
import torch

def _softmax(x, axis=-1):
    return torch.softmax(x, dim=axis)
def _gelu(x):
    return torch.nn.functional.gelu(x, approximate="tanh")
def _silu(x):
    return torch.nn.functional.silu(x)
def _sigmoid(x):
    return torch.sigmoid(x)
def _layernorm(x, axis=-1, eps=1e-5):
    m = x.mean(dim=axis, keepdim=True)
    v = x.var(dim=axis, keepdim=True, unbiased=False)
    return (x - m) / torch.sqrt(v + eps)
def _scatter_add(tgt, idx, src, axis=0):
    return tgt.clone().index_add_(axis, idx, src)
def _segment_sum(src, seg, n):
    out = torch.zeros((n,) + src.shape[1:], dtype=src.dtype)
    return out.index_add_(0, seg, src)
def _pad(x, pw):
    flat = tuple(v for pair in reversed(pw) for v in pair)
    return torch.nn.functional.pad(x, flat)

kernel_name = 'concat_heads__ssm_conv_s4__linear_attn_block__prompt'

def setup_inputs():

    _w = (lambda a: (lambda t: t.to(torch.bfloat16) if t.is_floating_point() else t)(torch.as_tensor(a)))
    def _A_setup():
        B, L, D, N = 1, 2048, 512, 128
        A_re = -(lambda _x: torch.exp(torch.as_tensor(_x)))((lambda *s: torch.randn(*s, dtype=torch.bfloat16) * 6.4)(D, N))
        A_im = torch.pi * (lambda *s: torch.randn(*s, dtype=torch.bfloat16) * 0.05)(D, N)
        B_re = (lambda *s: torch.randn(*s, dtype=torch.bfloat16) * 0.1)(D, N)
        B_im = (lambda *s: torch.randn(*s, dtype=torch.bfloat16) * 0.1)(D, N)
        C_re = (lambda *s: torch.randn(*s, dtype=torch.bfloat16) * 0.1)(D, N)
        C_im = (lambda *s: torch.randn(*s, dtype=torch.bfloat16) * 0.1)(D, N)
        log_dt = (lambda *s: torch.randn(*s, dtype=torch.bfloat16) * 0.05)(D) * 0.5 - 4.0
        Dskip = (lambda *s: torch.randn(*s, dtype=torch.bfloat16) * 0.05)(D)
        return {
            "u": _w((lambda *s: torch.randn(*s, dtype=torch.bfloat16) * 0.05)(B, L, D)),
            "A_re": _w(A_re),
            "A_im": _w(A_im),
            "B_re": _w(B_re),
            "B_im": _w(B_im),
            "C_re": _w(C_re),
            "C_im": _w(C_im),
            "log_dt": _w(log_dt),
            "Dskip": _w(Dskip),
        }
    _A_in = _A_setup()

    def _B_setup():
        B, S, D = 1, 2048, 512
        return {
            "x": _w((lambda *s: torch.randn(*s, dtype=torch.bfloat16) * 0.05)(B, S, D)),
            "wqkv": _w((lambda *s: torch.randn(*s, dtype=torch.bfloat16) * 0.4)(D, 3 * D)),
            "wo": _w((lambda *s: torch.randn(*s, dtype=torch.bfloat16) * 0.05)(D, D)),
        }
    _B_in = _B_setup()

    return {
        "A_u": _A_in["u"],
        "A_A_re": _A_in["A_re"],
        "A_A_im": _A_in["A_im"],
        "A_B_re": _A_in["B_re"],
        "A_B_im": _A_in["B_im"],
        "A_C_re": _A_in["C_re"],
        "A_C_im": _A_in["C_im"],
        "A_log_dt": _A_in["log_dt"],
        "A_Dskip": _A_in["Dskip"],
        "B_x": _B_in["x"],
        "B_wqkv": _B_in["wqkv"],
        "B_wo": _B_in["wo"],
    }

def reference(A_u, A_A_re, A_A_im, A_B_re, A_B_im, A_C_re, A_C_im, A_log_dt, A_Dskip, B_x, B_wqkv, B_wo):
    def _A_ref(u, A_re, A_im, B_re, B_im, C_re, C_im, log_dt, Dskip):
        Bsz, L, D = u.shape
        dt = torch.exp(log_dt)[:, None]
        A = A_re + 1j * A_im
        Bc = B_re + 1j * B_im
        Cc = C_re + 1j * C_im
        logdA = dt * A
        dB = dt * Bc
        l = (lambda x, dt: x.to(dt))(torch.arange(L), A_re.dtype)
        P = torch.exp(logdA[:, :, None] * l[None, None, :])
        K = torch.einsum("dn,dnl,dn->dl", Cc, P, dB).real
        L2 = 2 * L
        Kp = _pad(K, ((0, 0), (0, L)))
        up = (lambda x, *d: x.permute(*d))(u, 0, 2, 1)
        up = _pad(up, ((0, 0), (0, 0), (0, L)))
        Kf = (lambda x, axes=(-2,-1): torch.fft.rfft2(x.float(), dim=axes))(Kp[:, None, :], axes=(-2, -1))
        Uf = (lambda x, axes=(-2,-1): torch.fft.rfft2(x.float(), dim=axes))(up[:, :, None, :], axes=(-2, -1))
        Yf = Uf * Kf[None, :, :, :]
        y = (lambda x, s, axes=(-2,-1): torch.fft.irfft2(x, s=s, dim=axes).to(torch.bfloat16))(Yf, (1, L2), axes=(-2, -1))[:, :, 0, :L]
        y = (lambda x, *d: x.permute(*d))(y, 0, 2, 1) + u * Dskip[None, None, :]
        return y

    def _B_ref(x, wqkv, wo):
        B, S, D = x.shape
        H = 32; Dh = D // H
        qkv = (lambda x, *d: x.permute(*d))((x @ wqkv).reshape(B, S, 3, H, Dh), 2, 0, 3, 1, 4)
        q, k, v = qkv[0], qkv[1], qkv[2]
        phi = lambda t: torch.where(t > 0, t + 1, torch.exp(t)) + 1e-6
        pq, pk = phi(q), phi(k)
        kv = torch.einsum("bhsd,bhse->bhde", pk, v)
        z = torch.einsum("bhsd->bhd", pk)
        num = torch.einsum("bhqd,bhde->bhqe", pq, kv)
        den = torch.einsum("bhqd,bhd->bhq", pq, z)[..., None] + 1e-6
        o = num / den
        return (lambda x, *d: x.permute(*d))(o, 0, 2, 1, 3).reshape(B, S, D) @ wo

    a = _A_ref(A_u, A_A_re, A_A_im, A_B_re, A_B_im, A_C_re, A_C_im, A_log_dt, A_Dskip)
    b = _B_ref(B_x, B_wqkv, B_wo)
    return torch.concatenate([a, b], axis=-1)
```

```cpp
#include <cuda_runtime.h>
#include <cuda_bf16.h>
#include <cuda.h>
#include <stdint.h>

namespace {

constexpr int L_ = 2048;
constexpr int NTHREADS = 512;
constexpr int SPIN_LIMIT = 1 << 20;
#define UHOP_AT 3
#define PF_T0 900
#define PF_DT 300
#define GO_KB 2

constexpr int STAGE1 = 40960, XB1 = 16384, WB1 = 8192;
constexpr int QT_OFF = 0, KT_OFF = 16384, VT_OFF = 32768;
constexpr int PQ_OFF = 0;
constexpr int WO_OFF = 65536;
constexpr int WO2_OFF = 81920, WO2_HALF = 57344;
constexpr int CH_BYTES = 29568;
constexpr int PARK_PITCH = 528;
constexpr int X1E = 3680, EO1 = 4608;
constexpr int X2E = X1E + 2 * EO1, EO2 = 3328;
constexpr int X3E = X2E + 2 * EO2, EO3 = 2688, HS3 = 1344;
constexpr int Y0_REL = X3E + 2 * EO3;
static_assert(Y0_REL + 4352 <= CH_BYTES, "channel region");
constexpr int CH012_OFF = 122880, CH3_OFF = 81920;
constexpr int U_OFF = CH012_OFF + 3 * CH_BYTES;
constexpr int U_CH = 4960, U_PRE = 608;
constexpr int KVS_OFF = 111616;
constexpr int STG_OFF = 211968;
constexpr int BAR_OFF = 231424;
constexpr int MISC_OFF = BAR_OFF + 400;
constexpr int CLK_OFF = MISC_OFF + 192;
constexpr int SMEM_BYTES = 232448;
static_assert(U_OFF + 4 * U_CH <= BAR_OFF && STG_OFF + 16384 <= BAR_OFF && STG_OFF >= U_OFF, "u region");

enum { B_FULL1 = 0, B_GO = 3, B_UTILE = 4, B_UT = 5, B_EPOCH = 6, B_KVOK = 7, B_YT = 8, B_TAPS = 9, B_PQ = 13, B_WO = 21, B_YRDY = 26, B_KM = 27,
       B_EMPTY1 = 31, B_S2FREE = 34, B_SOUT = 35, B_ODONE = 36, B_YOUT = 37, B_T1 = 38, B_QT = 39, B_KV = 40, B_YST = 41, B_COUNT = 42 };

__device__ __nv_bfloat16 g_UT[512 * 2176];
__device__ __nv_bfloat16 g_YT[512 * 2048];
__device__ __nv_bfloat16 g_Q[2048 * 512];
__device__ float g_KV[2][32 * 256 + 512];
__device__ unsigned int g_cnt[32 * 40];
#define CLK(i) do { } while (0)
#define CLKL(i) do { } while (0)

struct Params {
    const __nv_bfloat16 *A_re, *A_im, *B_re, *B_im, *C_re, *C_im, *log_dt, *Dskip, *wo;
    int zero;
};

__device__ __forceinline__ uint32_t smem_u32(const void* p) { return (uint32_t)__cvta_generic_to_shared(p); }
__device__ __forceinline__ bool elect_one() { uint32_t p; asm volatile("{\n.reg .pred P;\nelect.sync _|P, 0xffffffff;\nselp.u32 %0, 1, 0, P;\n}" : "=r"(p)); return p != 0; }
__device__ __forceinline__ void mbar_init(uint32_t bar, uint32_t cnt) { asm volatile("mbarrier.init.shared::cta.b64 [%0], %1;" :: "r"(bar), "r"(cnt) : "memory"); }
__device__ __forceinline__ void mbar_expect_tx(uint32_t bar, uint32_t bytes) { asm volatile("mbarrier.arrive.expect_tx.shared::cta.b64 _, [%0], %1;" :: "r"(bar), "r"(bytes) : "memory"); }
__device__ __forceinline__ void mbar_arrive(uint32_t bar) { asm volatile("mbarrier.arrive.shared::cta.b64 _, [%0];" :: "r"(bar) : "memory"); }
__device__ __forceinline__ void mbar_wait(uint32_t bar, uint32_t parity) {
    asm volatile("{\n.reg .pred p;\n.reg .u32 n;\nmov.u32 n, %2;\nWL_%=:\nmbarrier.try_wait.parity.shared::cta.b64 p, [%0], %1;\n@p bra WD_%=;\n"
                 "sub.u32 n, n, 1;\nsetp.ne.u32 p, n, 0;\n@p bra WL_%=;\nWD_%=:\n}" :: "r"(bar), "r"(parity), "n"(SPIN_LIMIT) : "memory");
}
__device__ __forceinline__ void tma2d(uint32_t dst, const CUtensorMap* map, int c0, int c1, uint32_t bar) {
    asm volatile("cp.async.bulk.tensor.2d.shared::cluster.global.mbarrier::complete_tx::bytes [%0], [%1, {%3, %4}], [%2];"
        :: "r"(dst), "l"(map), "r"(bar), "r"(c0), "r"(c1) : "memory");
}
__device__ __forceinline__ void bulk_g2s(uint32_t dst, const void* src, uint32_t bytes, uint32_t bar) {
    asm volatile("cp.async.bulk.shared::cluster.global.mbarrier::complete_tx::bytes [%0], [%1], %2, [%3];" :: "r"(dst), "l"(src), "r"(bytes), "r"(bar) : "memory");
}
__device__ __forceinline__ void tma2d_store(const CUtensorMap* map, int c0, int c1, uint32_t src) {
    asm volatile("cp.async.bulk.tensor.2d.global.shared::cta.bulk_group [%0, {%2, %3}], [%1];" :: "l"(map), "r"(src), "r"(c0), "r"(c1) : "memory");
}
__device__ __forceinline__ void tma3d_store(const CUtensorMap* map, int c0, int c1, int c2, uint32_t src) {
    asm volatile("cp.async.bulk.tensor.3d.global.shared::cta.bulk_group [%0, {%2, %3, %4}], [%1];" :: "l"(map), "r"(src), "r"(c0), "r"(c1), "r"(c2) : "memory");
}
__device__ __forceinline__ void tma_prefetch2d(const CUtensorMap* map, int c0, int c1) {
    asm volatile("cp.async.bulk.prefetch.tensor.2d.L2.global.tile [%0, {%1, %2}];" :: "l"(map), "r"(c0), "r"(c1) : "memory");
}
__device__ __forceinline__ void bulk_commit() { asm volatile("cp.async.bulk.commit_group;" ::: "memory"); }
__device__ __forceinline__ void bulk_wait0() { asm volatile("cp.async.bulk.wait_group 0;" ::: "memory"); }
__device__ __forceinline__ void bulk_wait0_read() { asm volatile("cp.async.bulk.wait_group.read 0;" ::: "memory"); }
__device__ __forceinline__ void fence_async_smem() { asm volatile("fence.proxy.async.shared::cta;" ::: "memory"); }
__device__ __forceinline__ void fence_async_global() { asm volatile("fence.proxy.async.global;" ::: "memory"); }
__device__ __forceinline__ void bar_sync(int id, int n) { asm volatile("bar.sync %0, %1;" :: "r"(id), "r"(n) : "memory"); }
__device__ __forceinline__ void bar_arrive(int id, int n) { asm volatile("bar.arrive %0, %1;" :: "r"(id), "r"(n) : "memory"); }
__device__ __forceinline__ void group_barrier(unsigned int* p, unsigned int target) {
    asm volatile("fence.proxy.async.global;\nred.relaxed.gpu.global.add.u32 [%0], 1;" :: "l"(p) : "memory");
    asm volatile("{\n.reg .pred p;\n.reg .u32 n, v;\nmov.u32 n, %2;\nPL_%=:\nld.relaxed.gpu.global.u32 v, [%0];\nsub.u32 v, v, %1;\nsetp.ge.s32 p, v, 0;\n@p bra PD_%=;\n"
                 "sub.u32 n, n, 1;\nsetp.ne.u32 p, n, 0;\n@p bra PL_%=;\nPD_%=:\n"
                 "ld.acquire.gpu.global.u32 v, [%0];\n"
                 "fence.proxy.async.global;\n}" :: "l"(p), "r"(target), "n"(SPIN_LIMIT) : "memory");
}
__device__ __forceinline__ void bulk_s2g(void* dst, uint32_t src, uint32_t bytes) {
    asm volatile("cp.async.bulk.global.shared::cta.bulk_group [%0], [%1], %2;" :: "l"(dst), "r"(src), "r"(bytes) : "memory");
}
__device__ __forceinline__ void bulk_red_f32(void* dst, uint32_t src, uint32_t bytes) {
    asm volatile("cp.reduce.async.bulk.global.shared::cta.bulk_group.add.f32 [%0], [%1], %2;" :: "l"(dst), "r"(src), "r"(bytes) : "memory");
}
__device__ __forceinline__ void wg_fence() { asm volatile("wgmma.fence.sync.aligned;" ::: "memory"); }
__device__ __forceinline__ void wg_commit() { asm volatile("wgmma.commit_group.sync.aligned;" ::: "memory"); }
template <int N> __device__ __forceinline__ void wg_wait() { asm volatile("wgmma.wait_group.sync.aligned %0;" :: "n"(N) : "memory"); }
__device__ __forceinline__ uint64_t mkdesc(uint32_t saddr, uint32_t lbo) {
    return (uint64_t)((saddr & 0x3FFFF) >> 4) | ((uint64_t)(lbo >> 4) << 16) | ((uint64_t)(1024 >> 4) << 32) | ((uint64_t)1 << 62);
}
#define R4(b) "+f"(d[b]), "+f"(d[b + 1]), "+f"(d[b + 2]), "+f"(d[b + 3])
#define R16(b) R4(b), R4(b + 4), R4(b + 8), R4(b + 12)
__device__ __forceinline__ void wgmma192(float* d, uint64_t da, uint64_t db, int scale_d) {
    asm volatile("{\n.reg .pred p;\nsetp.ne.b32 p, %98, 0;\n"
        "wgmma.mma_async.sync.aligned.m64n192k16.f32.bf16.bf16 {"
        "%0,%1,%2,%3,%4,%5,%6,%7,%8,%9,%10,%11,%12,%13,%14,%15,%16,%17,%18,%19,%20,%21,%22,%23,%24,%25,%26,%27,%28,%29,%30,%31,"
        "%32,%33,%34,%35,%36,%37,%38,%39,%40,%41,%42,%43,%44,%45,%46,%47,%48,%49,%50,%51,%52,%53,%54,%55,%56,%57,%58,%59,%60,%61,%62,%63,"
        "%64,%65,%66,%67,%68,%69,%70,%71,%72,%73,%74,%75,%76,%77,%78,%79,%80,%81,%82,%83,%84,%85,%86,%87,%88,%89,%90,%91,%92,%93,%94,%95"
        "}, %96, %97, p, 1, 1, 0, 1;\n}\n"
        : R16(0), R16(16), R16(32), R16(48), R16(64), R16(80) : "l"(da), "l"(db), "r"(scale_d));
}
__device__ __forceinline__ void wgmma64(float* d, uint64_t da, uint64_t db, int scale_d) {
    asm volatile("{\n.reg .pred p;\nsetp.ne.b32 p, %34, 0;\n"
        "wgmma.mma_async.sync.aligned.m64n64k16.f32.bf16.bf16 {"
        "%0,%1,%2,%3,%4,%5,%6,%7,%8,%9,%10,%11,%12,%13,%14,%15,%16,%17,%18,%19,%20,%21,%22,%23,%24,%25,%26,%27,%28,%29,%30,%31"
        "}, %32, %33, p, 1, 1, 0, 1;\n}\n"
        : R16(0), R16(16) : "l"(da), "l"(db), "r"(scale_d));
}
__device__ __forceinline__ void mma16816(float* d, uint32_t a0, uint32_t a1, uint32_t a2, uint32_t a3, uint32_t b0, uint32_t b1) {
    asm volatile("mma.sync.aligned.m16n8k16.row.col.f32.bf16.bf16.f32 {%0,%1,%2,%3}, {%4,%5,%6,%7}, {%8,%9}, {%0,%1,%2,%3};"
        : "+f"(d[0]), "+f"(d[1]), "+f"(d[2]), "+f"(d[3]) : "r"(a0), "r"(a1), "r"(a2), "r"(a3), "r"(b0), "r"(b1));
}
__device__ __forceinline__ void mma16816c(float* d, const uint32_t* a, uint32_t b0, uint32_t b1, float c) {
    asm volatile("mma.sync.aligned.m16n8k16.row.col.f32.bf16.bf16.f32 {%0,%1,%2,%3}, {%4,%5,%6,%7}, {%8,%9}, {%10,%10,%10,%10};"
        : "=f"(d[0]), "=f"(d[1]), "=f"(d[2]), "=f"(d[3]) : "r"(a[0]), "r"(a[1]), "r"(a[2]), "r"(a[3]), "r"(b0), "r"(b1), "f"(c));
}
__device__ __forceinline__ void ldsm4(uint32_t addr, uint32_t* r) {
    asm volatile("ldmatrix.sync.aligned.m8n8.x4.shared.b16 {%0,%1,%2,%3}, [%4];" : "=r"(r[0]), "=r"(r[1]), "=r"(r[2]), "=r"(r[3]) : "r"(addr) : "memory");
}
__device__ __forceinline__ void ldsm4t(uint32_t addr, uint32_t* r) {
    asm volatile("ldmatrix.sync.aligned.m8n8.x4.trans.shared.b16 {%0,%1,%2,%3}, [%4];" : "=r"(r[0]), "=r"(r[1]), "=r"(r[2]), "=r"(r[3]) : "r"(addr) : "memory");
}
__device__ __forceinline__ void stsm4(uint32_t addr, uint32_t r0, uint32_t r1, uint32_t r2, uint32_t r3) {
    asm volatile("stmatrix.sync.aligned.m8n8.x4.shared.b16 [%0], {%1,%2,%3,%4};" :: "r"(addr), "r"(r0), "r"(r1), "r"(r2), "r"(r3) : "memory");
}
__device__ __forceinline__ uint32_t pack_bf16(float lo, float hi) { uint32_t r; asm("cvt.rn.bf16x2.f32 %0, %1, %2;" : "=r"(r) : "f"(hi), "f"(lo)); return r; }
__device__ __forceinline__ uint32_t hadd2(uint32_t a, uint32_t b) { uint32_t r; asm("add.rn.bf16x2 %0, %1, %2;" : "=r"(r) : "r"(a), "r"(b)); return r; }
__device__ __forceinline__ float bf_lo(uint32_t v) { return __uint_as_float(v << 16); }
__device__ __forceinline__ float bf_hi(uint32_t v) { return __uint_as_float(v & 0xffff0000u); }
__device__ __forceinline__ uint32_t lds32(uint32_t a) { uint32_t v; asm volatile("ld.shared.b32 %0, [%1];" : "=r"(v) : "r"(a) : "memory"); return v; }
__device__ __forceinline__ void lds128(uint32_t a, uint32_t* r) { asm volatile("ld.shared.v4.b32 {%0,%1,%2,%3}, [%4];" : "=r"(r[0]), "=r"(r[1]), "=r"(r[2]), "=r"(r[3]) : "r"(a) : "memory"); }
__device__ __forceinline__ void lds128v(uint32_t a, uint32_t* r) { asm volatile("ld.volatile.shared.v4.b32 {%0,%1,%2,%3}, [%4];" : "=r"(r[0]), "=r"(r[1]), "=r"(r[2]), "=r"(r[3]) : "r"(a) : "memory"); }
__device__ __forceinline__ uint32_t lds32v(uint32_t a) { uint32_t v; asm volatile("ld.volatile.shared.b32 %0, [%1];" : "=r"(v) : "r"(a) : "memory"); return v; }
__device__ __forceinline__ void lds128f(uint32_t a, float* r) { asm volatile("ld.shared.v4.f32 {%0,%1,%2,%3}, [%4];" : "=f"(r[0]), "=f"(r[1]), "=f"(r[2]), "=f"(r[3]) : "r"(a) : "memory"); }
__device__ __forceinline__ void sts16(uint32_t a, uint32_t v) { asm volatile("st.shared.b16 [%0], %1;" :: "r"(a), "h"((unsigned short)v) : "memory"); }
__device__ __forceinline__ void sts32(uint32_t a, uint32_t v) { asm volatile("st.shared.b32 [%0], %1;" :: "r"(a), "r"(v) : "memory"); }
__device__ __forceinline__ void sts64(uint32_t a, uint32_t x, uint32_t y) { asm volatile("st.shared.v2.b32 [%0], {%1,%2};" :: "r"(a), "r"(x), "r"(y) : "memory"); }
__device__ __forceinline__ void sts64f(uint32_t a, float x, float y) { asm volatile("st.shared.v2.f32 [%0], {%1,%2};" :: "r"(a), "f"(x), "f"(y) : "memory"); }
__device__ __forceinline__ void sts128(uint32_t a, uint32_t x, uint32_t y, uint32_t z, uint32_t w) { asm volatile("st.shared.v4.b32 [%0], {%1,%2,%3,%4};" :: "r"(a), "r"(x), "r"(y), "r"(z), "r"(w) : "memory"); }
__device__ __forceinline__ float ex2f(float x) { float y; asm("ex2.approx.ftz.f32 %0, %1;" : "=f"(y) : "f"(x)); return y; }
__device__ __forceinline__ float rcpf(float x) { float y; asm("rcp.approx.ftz.f32 %0, %1;" : "=f"(y) : "f"(x)); return y; }
__device__ __forceinline__ float phi_fn(float x) {
    const float th = x * 0.7213475204444817f;
    return fmaf(x, 0.5f, fmaf(fabsf(x), 0.5f, 1e-6f)) + ex2f(th - fabsf(th));
}
__device__ __forceinline__ uint32_t bf16_bits(float x) { return pack_bf16(x, 0.f); }
__device__ __forceinline__ float bf16_round(float x) { return bf_lo(pack_bf16(x, 0.f)); }

struct C2 { float r, i; };
__device__ __forceinline__ C2 cmul(C2 a, C2 b) { C2 o; o.r = fmaf(a.r, b.r, -(a.i * b.i)); o.i = fmaf(a.r, b.i, a.i * b.r); return o; }
__device__ __forceinline__ C2 csq(C2 a) { C2 o; o.r = fmaf(a.r, a.r, -(a.i * a.i)); o.i = (a.r + a.r) * a.i; return o; }
__device__ __forceinline__ C2 cexp_t(float sg2, float wt, float t) {
    const float m = ex2f(sg2 * t);
    float r = wt * t; r -= rintf(r);
    const float a = r * 6.283185307179586f;
    C2 o; o.r = m * __cosf(a); o.i = m * __sinf(a); return o;
}
__device__ __noinline__ void transpose_inplace(uint32_t base, int aw, int lane) {
    const int mi = lane >> 3, rr = lane & 7;
    const int srow = aw * 16 + (mi & 1) * 8 + rr;
    uint32_t v[8][4];
#pragma unroll
    for (int i = 0; i < 8; i++) ldsm4t(base + (i >> 2) * 8192 + srow * 128 + ((((i & 3) * 2 + (mi >> 1)) ^ rr) << 4), v[i]);
    bar_sync(12, 128);
    const uint32_t d = base + ((mi >> 1) * 8 + rr) * 128 + (((aw * 2 + (mi & 1)) ^ rr) << 4);
#pragma unroll
    for (int i = 0; i < 8; i++) stsm4(d + (i >> 2) * 8192 + (i & 3) * 2048, v[i][0], v[i][1], v[i][2], v[i][3]);
    fence_async_smem();
    __syncwarp();
}
__device__ __forceinline__ uint32_t u_chunk(uint32_t ub, int chi) { return ub + U_PRE + (chi + (chi >> 4)) * 16; }

template <int NTILE, int BMIN, int NSET>
__device__ __forceinline__ void conv_octave(uint32_t fq, uint32_t xa, uint32_t ya, uint32_t set_stride) {
    uint32_t Qe[5][4], Qo[5][4];
    {
        uint32_t Fe[11], Fo[11];
#pragma unroll
        for (int i = 0; i < 11; i++) { Fe[i] = lds32(fq - 16 * i); Fo[i] = lds32(fq + 416 - 16 * i); }
#pragma unroll
        for (int k = 0; k < 5; k++) {
            Qe[k][0] = Fe[2 * k + 1]; Qe[k][1] = Fe[2 * k + 2]; Qe[k][2] = Fe[2 * k]; Qe[k][3] = Fe[2 * k + 1];
            Qo[k][0] = Fo[2 * k + 1]; Qo[k][1] = Fo[2 * k + 2]; Qo[k][2] = Fo[2 * k]; Qo[k][3] = Fo[2 * k + 1];
#pragma unroll
            for (int i = 0; i < 4; i++) { asm volatile("mov.b32 %0, %0;" : "+r"(Qe[k][i])); asm volatile("mov.b32 %0, %0;" : "+r"(Qo[k][i])); }
        }
    }
    float acc[NSET][NTILE][4];
#pragma unroll
    for (int n = 0; n < NSET; n++)
#pragma unroll
        for (int i = 0; i < NTILE; i++) { acc[n][i][0] = acc[n][i][1] = acc[n][i][2] = acc[n][i][3] = 0.f; }
    uint32_t b[NSET][3][4];
#pragma unroll
    for (int n = 0; n < NSET; n++) { ldsm4t(xa + n * set_stride + BMIN * 256, b[n][BMIN % 3]); ldsm4t(xa + n * set_stride + (BMIN + 1) * 256, b[n][(BMIN + 1) % 3]); }
#pragma unroll
    for (int be = BMIN; be < NTILE + 4; be++) {
#pragma unroll
        for (int n = 0; n < NSET; n++) {
            if (be + 2 < NTILE + 4) ldsm4t(xa + n * set_stride + (be + 2) * 256, b[n][(be + 2) % 3]);
            if (BMIN == 0 || be > BMIN || n == NSET - 1) {
#pragma unroll
                for (int k = 0; k < 5; k++) { const int tl = be - 4 + k; if (tl >= 0 && tl < NTILE) mma16816(acc[n][tl], Qe[k][0], Qe[k][1], Qe[k][2], Qe[k][3], b[n][be % 3][0], b[n][be % 3][1]); }
            }
        }
        if (BMIN == 0 || be > BMIN) {
#pragma unroll
            for (int n = 0; n < NSET; n++)
#pragma unroll
                for (int k = 0; k < 5; k++) { const int tl = be - 4 + k; if (tl >= 0 && tl < NTILE) mma16816(acc[n][tl], Qo[k][0], Qo[k][1], Qo[k][2], Qo[k][3], b[n][be % 3][2], b[n][be % 3][3]); }
        }
        if (be >= 5) {
#pragma unroll
            for (int n = 0; n < NSET; n++) { const float* a = acc[n][be - 5]; sts32(ya + n * set_stride + (be - 1) * 256, pack_bf16(a[0], a[1])); sts32(ya + n * set_stride + (be - 1) * 256 + 128, pack_bf16(a[2], a[3])); }
        }
    }
#pragma unroll
    for (int n = 0; n < NSET; n++) { const float* a = acc[n][NTILE - 1]; sts32(ya + n * set_stride + (NTILE + 3) * 256, pack_bf16(a[0], a[1])); sts32(ya + n * set_stride + (NTILE + 3) * 256 + 128, pack_bf16(a[2], a[3])); }
}

__global__ void __launch_bounds__(NTHREADS, 1)
fused_kernel(const __grid_constant__ CUtensorMap mX, const __grid_constant__ CUtensorMap mW, const __grid_constant__ CUtensorMap mU,
             const __grid_constant__ CUtensorMap mUT, const __grid_constant__ CUtensorMap mQ, const __grid_constant__ CUtensorMap mWO,
             const __grid_constant__ CUtensorMap mWO2, const __grid_constant__ CUtensorMap mYT, const __grid_constant__ CUtensorMap mOut, const Params p) {
    extern __shared__ __align__(1024) unsigned char smem_raw[];
    const uint32_t sb = smem_u32(smem_raw);
    const int lane = threadIdx.x & 31, hwarp = __shfl_sync(0xffffffffu, threadIdx.x >> 5, 0);
    const int warp = hwarp;
    const int g = lane >> 2, t = lane & 3, mi = lane >> 3, rr = lane & 7;
    const int mt = blockIdx.x & 15, nt = blockIdx.x >> 4;
    const uint32_t bars = sb + BAR_OFF;
    const uint32_t t0 = clock();
#define BAR(i) (bars + (i) * 8)

    if (warp == 12) {
        const bool leader = elect_one();
        if (leader) {
            mbar_init(BAR(B_FULL1), 1); mbar_init(BAR(B_FULL1 + 1), 1); mbar_init(BAR(B_FULL1 + 2), 1);
            asm volatile("fence.mbarrier_init.release.cluster;" ::: "memory");
        }
        __syncwarp();
        bar_arrive(0, NTHREADS);
        if (leader) {
#pragma unroll 1
            for (int kb = 0; kb < 3; kb++) {
                const uint32_t full = BAR(B_FULL1 + kb), sa = sb + kb * STAGE1;
                mbar_expect_tx(full, STAGE1);
                tma2d(sa, &mX, kb * 64, mt * 128, full);
#pragma unroll 1
                for (int j = 0; j < 3; j++) tma2d(sa + XB1 + j * WB1, &mW, j * 512 + nt * 64, kb * 64, full);
            }
            CLKL(30);
        }
        __syncwarp();
        bar_sync(13, 64);
    } else {
        if (warp < 12 && elect_one()) {
#pragma unroll 1
            for (int i = 3 + 4 * warp; i < min(7 + 4 * warp, (int)B_COUNT); i++) mbar_init(BAR(i), i < B_EMPTY1 ? 1 : (i < B_SOUT ? 2 : (i < B_T1 ? 4 : 8)));
            asm volatile("fence.mbarrier_init.release.cluster;" ::: "memory");
        }
        __syncwarp();
        bar_sync(0, NTHREADS);
        if (warp == 13) bar_arrive(13, 64);
    }

    if (warp < 8) {
        asm volatile("setmaxnreg.inc.sync.aligned.u32 160;");
        const int wg = warp >> 2, w4 = warp & 3;
        const uint32_t wrow = sb + (wg * 64 + w4 * 16) * 128;
        const uint32_t frow = (uint32_t)(((mi & 1) * 8 + rr) * 128);
        {
            float acc[96];
            int s = 0, ph = 0;
#pragma unroll 1
            for (int kb = 0; kb < 8; kb++) {
                mbar_wait(BAR(B_FULL1 + s), ph);
                if (kb == GO_KB && warp == 0 && lane == 0) mbar_arrive(BAR(B_GO));
                if (warp == 0) CLK(37 + kb);

                const uint64_t da = mkdesc(sb + s * STAGE1 + wg * (XB1 / 2), 16), db = mkdesc(sb + s * STAGE1 + XB1, WB1);
                wg_fence();
#pragma unroll
                for (int j = 0; j < 4; j++) wgmma192(acc, da + j * 2, db + j * 128, (kb | j) ? 1 : 0);
                wg_commit();
                if (kb > 0) {
                    wg_wait<1>();
                    if (kb <= 6 && w4 == 0 && lane == 0) mbar_arrive(BAR(kb == 6 ? B_S2FREE : B_EMPTY1 + (s == 0 ? 2 : s - 1)));
                }
                if (++s == 3) { s = 0; ph ^= 1; }
            }
            wg_wait<0>();
            CLK(1 + wg);
            if (lane == 0) mbar_arrive(BAR(B_T1));
            bar_sync(1, 256);
#pragma unroll
            for (int jj = 0; jj < 12; jj++) {
                const int j = jj < 8 ? jj + 4 : jj - 8;
                const int a = j * 8;
                float v[8];
#pragma unroll
                for (int i = 0; i < 8; i++) v[i] = j < 8 ? phi_fn(acc[a + i]) : acc[a + i];
                stsm4(wrow + frow + (j >> 2) * 16384 + ((((j & 3) * 2 + (mi >> 1)) ^ rr) << 4), pack_bf16(v[0], v[1]), pack_bf16(v[2], v[3]),
                      pack_bf16(v[4], v[5]), pack_bf16(v[6], v[7]));
                if (j < 8 && p.zero) asm volatile("trap;");
            }
                        fence_async_smem(); __syncwarp();
            if (lane == 0) mbar_arrive(BAR(B_QT));
                    }
        bar_sync(1, 256);
        {
            const int hh = warp >> 1, dh = warp & 1;
            float ckv[2][4], cz[2][4];
#pragma unroll
            for (int i = 0; i < 4; i++) { ckv[0][i] = ckv[1][i] = cz[0][i] = cz[1][i] = 0.f; }
            const uint32_t ones = 0x3f803f80u;
            const uint32_t av = sb + VT_OFF + ((mi >> 1) * 8 + rr) * 128 + (((hh * 2 + (mi & 1)) ^ rr) << 4);
            const uint32_t ak = sb + KT_OFF + (mi * 8 + rr) * 128 + (((hh * 2 + dh) ^ rr) << 4);
            uint32_t fa[8][4], fb[4][4];
#pragma unroll
            for (int ks = 0; ks < 4; ks++) { ldsm4t(ak + ks * 4096, fb[ks]); ldsm4t(av + ks * 4096, fa[2 * ks]); ldsm4t(av + ks * 4096 + 2048, fa[2 * ks + 1]); }
#pragma unroll
            for (int ks = 0; ks < 4; ks++) {
                mma16816(ckv[0], fa[2 * ks][0], fa[2 * ks][1], fa[2 * ks][2], fa[2 * ks][3], fb[ks][0], fb[ks][1]);
                mma16816(ckv[1], fa[2 * ks + 1][0], fa[2 * ks + 1][1], fa[2 * ks + 1][2], fa[2 * ks + 1][3], fb[ks][2], fb[ks][3]);
                mma16816(cz[0], ones, ones, ones, ones, fb[ks][0], fb[ks][1]);
                mma16816(cz[1], ones, ones, ones, ones, fb[ks][2], fb[ks][3]);
            }
                        const uint32_t ks_ = sb + KVS_OFF + (hh * 256 + g * 16 + dh * 8 + 2 * t) * 4;
            sts64f(ks_, ckv[0][0] + ckv[1][0], ckv[0][1] + ckv[1][1]);
            sts64f(ks_ + 512, ckv[0][2] + ckv[1][2], ckv[0][3] + ckv[1][3]);
            if (g == 0) sts64f(sb + KVS_OFF + 4096 + (hh * 16 + dh * 8 + 2 * t) * 4, cz[0][0] + cz[1][0], cz[0][1] + cz[1][1]);
            fence_async_smem();
            __syncwarp();
            if (lane == 0) mbar_arrive(BAR(B_KV));
            CLK(3 + wg);
        }
        const int c = w4;
        const uint32_t ub = sb + U_OFF + c * U_CH, cb_ = sb + (c < 3 ? CH012_OFF + c * CH_BYTES : CH3_OFF);
        mbar_wait(BAR(B_KM + c), 0);
        mbar_wait(BAR(B_UT), 0);
        if (warp == 0) CLK(36);
        int chi = wg * 32 - 32 + lane;
        uint32_t ul[4];
#pragma unroll
        for (int q = 0; q < 4; q++) ul[q] = u_chunk(ub, chi - 2 + q);
        const uint32_t x1s = (lane & 4) * 4;
        uint32_t a3 = cb_ + X3E + (chi & 1) * HS3 + ((chi >> 1) + 16) * 16, a2 = cb_ + X2E + (chi + 16) * 16, a1 = cb_ + X1E + (2 * chi + 64) * 16;
#pragma unroll 1
        for (int it = 0; it < 4; it++, chi += 64, a3 += 512, a2 += 1024, a1 += 2048) {
            const int chi0 = it * 64 + wg * 32 - 32;
            uint32_t r[16];
#pragma unroll
            for (int q = 0; q < 4; q++) { lds128v(ul[q], r + 4 * q); ul[q] += 1088; }
            uint32_t sh[13], w2[12], w4[12], e4[4], o4[4];
#pragma unroll
            for (int k = 2; k <= 12; k++) sh[k] = __byte_perm(r[k], r[k + 1], 0x5432);
#pragma unroll
            for (int p = 6; p < 12; p++) w2[p] = hadd2(hadd2(sh[p - 1], sh[p]), r[p]);
            if (chi0 < 192) {
#pragma unroll
                for (int p = 8; p < 12; p++) w4[p] = hadd2(w2[p], hadd2(r[p - 1], r[p + 1]));
                if (chi0 < 128) {
#pragma unroll
                    for (int p = 4; p < 8; p++) {
                        const uint32_t w2p = p < 6 ? hadd2(hadd2(sh[p - 1], sh[p]), r[p]) : w2[p];
                        o4[p - 4] = hadd2(hadd2(w2p, hadd2(r[p - 1], r[p + 1])), hadd2(sh[p - 2], sh[p + 1]));
                        e4[p - 4] = hadd2(hadd2(w4[p + 4], hadd2(sh[p + 2], sh[p + 5])), hadd2(r[p + 2], r[p + 6]));
                    }
                    sts128(a3, e4[0], e4[1], e4[2], e4[3]);
                    sts128(a3 + EO3, o4[0], o4[1], o4[2], o4[3]);
                }
                if (chi >= -16) {
                    sts128(a2, w4[8], w4[9], w4[10], w4[11]);
                    sts128(a2 + EO2, w2[6], w2[7], w2[8], w2[9]);
                }
            }
#pragma unroll
            for (int h = 0; h < 2; h++) {
                if (h == 0 ? chi < 112 : chi >= 80) {
                    const uint32_t a = a1 + (h ? 8 - 3584 : 0) + x1s, b = a1 + (h ? 8 - 3584 : 0) + 16 - x1s;
                    sts64(a, w2[8], w2[9]); sts64(b, w2[10], w2[11]);
                    sts64(a + EO1, r[7], r[8]); sts64(b + EO1, r[9], r[10]);
                }
            }
        }
        bar_sync(2 + c, 64);
        mbar_wait(BAR(B_TAPS + c), 0);
        CLK(5 + wg);
        {
            const uint32_t fq = cb_ + 1184 + (uint32_t)((g & 1) * 208 + (t - (g >> 1)) * 4) + 44 * 4;
            const uint32_t xl = ((mi & 1) * 8 + rr) * 16, yl = g * 16 + t * 4;
            if (wg == 0) conv_octave<14, 0, 1>(fq, cb_ + X1E + (mi >> 1) * EO1 + (xl ^ ((mi & 1) * 16)), cb_ + X1E + (t >> 1) * 64 + g * 8 + (t & 1) * 4, 0);
            else {
                conv_octave<12, 3, 1>(fq + 832, cb_ + X2E - 768 + (mi >> 1) * EO2 + xl, cb_ + X2E - 768 + yl, 0);
                conv_octave<4, 3, 2>(fq + 1664, cb_ + X3E - 768 + (mi >> 1) * EO3 + xl, cb_ + X3E - 768 + yl, HS3);
            }
        }
        CLK(7 + wg);
        bar_sync(6 + c, 96);
        {
            const float g256 = __uint_as_float(lds32(sb + MISC_OFF + 128 + c * 16)), g512 = __uint_as_float(lds32(sb + MISC_OFF + 128 + c * 16 + 4)),
                        g1024 = __uint_as_float(lds32(sb + MISC_OFF + 128 + c * 16 + 8));
            const uint32_t u01 = lds32(ub + U_PRE), u23 = lds32(ub + U_PRE + 4);
            const float s0 = bf_lo(u01), s1 = s0 + bf_hi(u01), s2 = s1 + bf_lo(u23), s3 = s2 + bf_hi(u23);
            int tau = wg * 32 + lane;
            uint32_t a0 = cb_ + Y0_REL + (tau + (tau >> 4)) * 16;
            uint32_t a2 = cb_ + X2E + 256 + (tau - 64) * 16;
            uint32_t a3 = cb_ + X3E + 256 + (tau & 1) * HS3 + ((tau - 128) >> 1) * 16;
            uint32_t ac = u_chunk(ub, tau - 128), ad = u_chunk(ub, tau - 127);
            __nv_bfloat16* yt = g_YT + (size_t)(nt * 64 + mt * 4 + c) * L_ + tau * 8;
#pragma unroll 1
            for (int it = 0; it < 4; it++, tau += 64, a0 += 1088, a2 += 1024, a3 += 512, ac += 1088, ad += 1088, yt += 512) {
                const int tau0 = it * 64 + wg * 32;
                uint32_t y[4];
                lds128(a0, y);
                float v[8];
#pragma unroll
                for (int i = 0; i < 4; i++) { v[2 * i] = bf_lo(y[i]); v[2 * i + 1] = bf_hi(y[i]); }
                if (tau0 >= 32) {
                    const int h = tau >= 144, r = tau - 32 - 112 * h;
                    uint32_t z[4];
                    lds128(cb_ + X1E + 1024 + (r >> 3) * 256 + ((r >> 2) & 1) * 128 + h * 64 + (r & 3) * 16, y);
                    if (tau0 >= 64) {
                        lds128(a2, z);
#pragma unroll
                        for (int i = 0; i < 4; i++) y[i] = hadd2(y[i], z[i]);
                        if (tau0 >= 128) {
                            lds128(a3, z);
#pragma unroll
                            for (int i = 0; i < 4; i++) y[i] = hadd2(y[i], z[i]);
                        }
                    }
#pragma unroll
                    for (int i = 0; i < 4; i++) { v[2 * i] += bf_lo(y[i]); v[2 * i + 1] += bf_hi(y[i]); }
                }
                if (tau0 >= 96) {
                    uint32_t pq[8];
                    lds128(ac, pq); lds128(ad, pq + 4);
#pragma unroll
                    for (int i = 0; i < 8; i++) v[i] = fmaf(g1024, ((i + 5) & 1) ? bf_hi(pq[(i + 5) >> 1]) : bf_lo(pq[(i + 5) >> 1]), v[i]);
                }
                if (tau == 31) v[7] = fmaf(g256, s0, v[7]);
                if (tau == 63) { v[6] = fmaf(g512, s0, v[6]); v[7] = fmaf(g512, s1, v[7]); }
                if (tau == 127) { v[4] = fmaf(g1024, s0, v[4]); v[5] = fmaf(g1024, s1, v[5]); v[6] = fmaf(g1024, s2, v[6]); v[7] = fmaf(g1024, s3, v[7]); }
                *reinterpret_cast<uint4*>(yt) = make_uint4(pack_bf16(v[0], v[1]), pack_bf16(v[2], v[3]), pack_bf16(v[4], v[5]), pack_bf16(v[6], v[7]));
            }
            __syncwarp();
            if (lane == 0) mbar_arrive(BAR(B_YST));
            CLK(9 + wg);
        }
        {
            float acc[32];
            mbar_wait(BAR(B_ODONE), 0);
            CLK(11 + wg);
            uint64_t da = mkdesc(sb + PQ_OFF, 16), db = mkdesc(sb + WO_OFF + wg * 8192, 4096);
            int ks = 0;
#pragma unroll 1
            for (int ch = 0; ch < 5; ch++) {
                mbar_wait(BAR(B_WO + ch), 0);
                if (warp == 0 && (ch == 1 || ch == 3)) CLK(ch == 1 ? 45 : 46);
                if (ch == 1) db = mkdesc(sb + WO2_OFF + wg * WO2_HALF, 4096);
                wg_fence();
#pragma unroll 1
                for (int i = 0; i < (ch ? 7 : 4); i++, ks++) {
                    wgmma64(acc, da, db, ks);
                    db += 128;
                    da += (ks & 3) == 3 ? 512 - 6 : 2;
                }
                wg_commit();
            }
            wg_wait<0>();
            CLK(13 + wg);
            bar_sync(1, 256);
            const uint32_t ob = sb + PQ_OFF + wg * 8192;
#pragma unroll
            for (int j = 0; j < 4; j++) {
                const int a = j * 8;
                stsm4(ob + w4 * 2048 + frow + (((j * 2 + (mi >> 1)) ^ rr) << 4), pack_bf16(acc[a], acc[a + 1]), pack_bf16(acc[a + 2], acc[a + 3]),
                      pack_bf16(acc[a + 4], acc[a + 5]), pack_bf16(acc[a + 6], acc[a + 7]));
            }
            fence_async_smem();
            bar_sync(10 + wg, 128);
            if (w4 == 0 && elect_one()) {
                tma2d_store(&mOut, 512 + (nt >> 1) * 128 + wg * 64, (2 * mt + (nt & 1)) * 64, ob);
                bulk_commit();
                bulk_wait0_read();
            }
            CLK(15 + wg);
        }
    } else if (warp < 12) {
        asm volatile("setmaxnreg.inc.sync.aligned.u32 152;");
        const int aw = warp - 8, m = aw * 32 + lane;
        const int ch0 = nt * 64 + mt * 4;
        uint32_t prm[4][4];
        {
            const int idx = ch0 * 128 + m;
            const unsigned short* const q0 = reinterpret_cast<const unsigned short*>(p.A_re) + idx; const unsigned short* const q1 = reinterpret_cast<const unsigned short*>(p.A_im) + idx;
            const unsigned short* const q2 = reinterpret_cast<const unsigned short*>(p.B_re) + idx; const unsigned short* const q3 = reinterpret_cast<const unsigned short*>(p.B_im) + idx;
            const unsigned short* const q4 = reinterpret_cast<const unsigned short*>(p.C_re) + idx; const unsigned short* const q5 = reinterpret_cast<const unsigned short*>(p.C_im) + idx;
            const unsigned short* const q6 = reinterpret_cast<const unsigned short*>(p.log_dt) + ch0;
            unsigned short raw[4][7];
#pragma unroll
            for (int c = 0; c < 4; c++) {
                raw[c][0] = __ldg(q0 + c * 128); raw[c][1] = __ldg(q1 + c * 128); raw[c][2] = __ldg(q2 + c * 128); raw[c][3] = __ldg(q3 + c * 128);
                raw[c][4] = __ldg(q4 + c * 128); raw[c][5] = __ldg(q5 + c * 128); raw[c][6] = __ldg(q6 + c);
            }
#pragma unroll
            for (int c = 0; c < 4; c++) {
                prm[c][0] = raw[c][0] | ((uint32_t)raw[c][1] << 16); prm[c][1] = raw[c][2] | ((uint32_t)raw[c][3] << 16);
                prm[c][2] = raw[c][4] | ((uint32_t)raw[c][5] << 16); prm[c][3] = (uint32_t)raw[c][6] << 16;
            }
        }
#pragma unroll 1
        for (int c = 0; c < 4; c++) {
            const uint32_t pa = prm[0][0], pb_ = prm[0][1], pc = prm[0][2];
            const float dt = bf16_round(expf(__uint_as_float(prm[0][3])));
#pragma unroll
            for (int i = 0; i < 4; i++) { prm[0][i] = prm[1][i]; prm[1][i] = prm[2][i]; prm[2][i] = prm[3][i]; }
            if (c == UHOP_AT) {
                mbar_wait(BAR(B_UTILE), 0);
                transpose_inplace(sb + STG_OFF, aw, lane);
                if (lane == 0) mbar_arrive(BAR(B_SOUT));
                CLK(17);
            }
            if (c == 3) mbar_wait(BAR(B_S2FREE), 0);
            const float sg2 = (dt * bf_lo(pa)) * 1.4426950408889634f, wt = (dt * bf_hi(pa)) * 0.15915494309189535f;
            C2 cc; { C2 cq = {bf_lo(pc), -bf_hi(pc)}, bq = {dt * bf_lo(pb_), -dt * bf_hi(pb_)}; cc = cmul(cq, bq); }
            const uint32_t pb = sb + (c < 3 ? CH012_OFF + c * CH_BYTES : CH3_OFF) + m * 4;
            auto gen8 = [&](int row, C2 base, C2 r1, C2 r2, C2 r3) {
                const C2 x1 = cmul(base, r1), x2 = cmul(base, r2), x4 = cmul(base, r3);
                const C2 x3 = cmul(x1, r2), x5 = cmul(x1, r3), x6 = cmul(x2, r3), x7 = cmul(x3, r3);
                const uint32_t a = pb + row * PARK_PITCH;
                sts32(a, pack_bf16(base.r, base.i)); sts32(a + PARK_PITCH, pack_bf16(x1.r, x1.i));
                sts32(a + 2 * PARK_PITCH, pack_bf16(x2.r, x2.i)); sts32(a + 3 * PARK_PITCH, pack_bf16(x3.r, x3.i));
                sts32(a + 4 * PARK_PITCH, pack_bf16(x4.r, x4.i)); sts32(a + 5 * PARK_PITCH, pack_bf16(x5.r, x5.i));
                sts32(a + 6 * PARK_PITCH, pack_bf16(x6.r, x6.i)); sts32(a + 7 * PARK_PITCH, pack_bf16(x7.r, x7.i));
                return x7;
            };
            const C2 E1 = cexp_t(sg2, -wt, 1.f), E128 = cexp_t(sg2, -wt, 128.f), E8 = cexp_t(sg2, wt, 8.f);
            const C2 E2 = csq(E1), E4 = csq(E2), E16 = csq(E8), E32 = csq(E16), E256 = csq(E128), E512 = csq(E256);
            const C2 one = {1.f, 0.f};
            gen8(0, one, E8, E16, E32);
            gen8(8, csq(E32), E8, E16, E32);
            gen8(16, cc, E1, E2, E4);
            gen8(24, cmul(cc, E128), E1, E2, E4);
            gen8(32, cmul(cc, E256), E2, E4, E128);
            gen8(40, cmul(cc, E512), E4, E128, E256);
            const C2 x7 = gen8(48, cmul(cc, csq(E512)), E128, E256, E512);
            float v = fmaf(x7.r, E128.r, -(x7.i * E128.i));
#pragma unroll
            for (int o = 16; o > 0; o >>= 1) v += __shfl_xor_sync(0xffffffffu, v, o);
            if (lane == 0) sts32(sb + MISC_OFF + 64 + (c * 4 + aw) * 4, __float_as_uint(v));
        }
        bar_sync(12, 128);
        CLK(18);
        const int c = aw;
        const float dsk = __bfloat162float(p.Dskip[ch0 + c]);
        float g2048 = 0.f;
#pragma unroll
        for (int w = 0; w < 4; w++) g2048 += __uint_as_float(lds32(sb + MISC_OFF + 64 + (c * 4 + w) * 4));
        const uint32_t cb_ = sb + (c < 3 ? CH012_OFF + c * CH_BYTES : CH3_OFF);
        mbar_wait(BAR(B_T1), 0);
        CLK(19);
        {
            float G[5][4];
#pragma unroll
            for (int n = 0; n < 5; n++) { G[n][0] = G[n][1] = G[n][2] = G[n][3] = 0.f; }
            uint32_t pa = cb_ + ((mi & 1) * 8 + rr) * PARK_PITCH + (mi >> 1) * 16;
            uint32_t pbb = cb_ + (16 + rr) * PARK_PITCH + mi * 16;
            uint32_t fa[2][2][4], fb[2][5][4];
            ldsm4(pa, fa[0][0]); ldsm4(pa + 32, fa[0][1]);
#pragma unroll
            for (int n = 0; n < 5; n++) ldsm4(pbb + n * 8 * PARK_PITCH, fb[0][n]);
#pragma unroll 1
            for (int ks = 0; ks < 4; ks++) {
#pragma unroll
                for (int h = 0; h < 2; h++) {
                    pa += 64; pbb += 64;
                    ldsm4(pa, fa[h ^ 1][0]); ldsm4(pa + 32, fa[h ^ 1][1]);
#pragma unroll
                    for (int n = 0; n < 5; n++) ldsm4(pbb + n * 8 * PARK_PITCH, fb[h ^ 1][n]);
#pragma unroll
                    for (int n = 0; n < 5; n++) mma16816(G[n], fa[h][0][0], fa[h][0][1], fa[h][0][2], fa[h][0][3], fb[h][n][0], fb[h][n][1]);
#pragma unroll
                    for (int n = 0; n < 5; n++) mma16816(G[n], fa[h][1][0], fa[h][1][1], fa[h][1][2], fa[h][1][3], fb[h][n][2], fb[h][n][3]);
                }
            }
            __syncwarp();
            if (lane == 0) mbar_arrive(BAR(B_KM + c));
            if (aw == 0) CLK(34);
#pragma unroll
            for (int i = 0; i < 8; i++) if (i < 7 || lane < 6) sts128(cb_ + (i * 32 + lane) * 16, 0u, 0u, 0u, 0u);
            const float g256 = __shfl_sync(0xffffffffu, G[2][0], 0), g512 = __shfl_sync(0xffffffffu, G[3][0], 0), g1024 = __shfl_sync(0xffffffffu, G[4][0], 0);
            if (aw == 0) CLK(35);
            if (lane == 0) G[0][0] += dsk;
            if (lane == 31) { G[1][3] -= g256; G[2][3] -= g512; G[3][3] -= g1024; }
            __syncwarp();
            if (lane < 3) sts32(sb + MISC_OFF + 128 + c * 16 + lane * 4, __float_as_uint(bf16_round(lane == 0 ? g256 : (lane == 1 ? g512 : g1024))));
            if (lane < 2) sts16(cb_ + 1184 + 4 * 416 + 32 + lane * 210, bf16_bits(g2048));
#pragma unroll
            for (int n = 0; n < 5; n++) {
                const uint32_t base = n < 2 ? cb_ + 2 * (272 - 128 * n) - 4 * t - 16 * g
                                    : n == 2 ? cb_ + 1184 + 160 - 64 * (t >> 1) - 2 * (t & 1) - 4 * g
                                    : n == 3 ? cb_ + 1184 + 832 + 160 - 32 * t - 2 * g
                                             : cb_ + 1184 + 1664 + 160 + 416 * (g & 1) - 32 * t - 2 * (g >> 1);
                const int dg = n < 2 ? -2 : (n < 4 ? 416 : -16), dq = n < 2 ? -128 : (n == 2 ? -32 : (n == 3 ? -16 : -8)), cs = n < 2 ? 594 : 210;
#pragma unroll
                for (int i = 0; i < 4; i++) {
                    const uint32_t hv = bf16_bits(G[n][i]);
                    sts16(base + (i & 1) * dg + (i >> 1) * dq, hv); sts16(base + (i & 1) * dg + (i >> 1) * dq + cs, hv);
                }
            }
            __syncwarp();
            if (lane == 0) mbar_arrive(BAR(B_TAPS + c));
        }
        CLK(20);
        const uint32_t ub = sb + U_OFF + c * U_CH;
        {
            const uint32_t fl = cb_ + (g & 1) * 592 + (t - (g >> 1)) * 4 + 136 * 4;
            uint32_t P0[34], P1[34];
            {
                uint32_t F[34];
#pragma unroll
                for (int i = 0; i < 34; i++) F[i] = lds32(fl - 16 * (i - 1));
#pragma unroll
                for (int i = 0; i < 34; i++) {
                    P0[i] = i <= 32 ? F[i + 1] : 0u; P1[i] = F[i];
                    asm volatile("mov.b32 %0, %0;" : "+r"(P0[i])); asm volatile("mov.b32 %0, %0;" : "+r"(P1[i]));
                }
            }
            mbar_wait(BAR(B_UT), 0);
            const uint32_t ua = ub + U_PRE + ((mi & 1) * 8 + rr) * 272 + (mi >> 1) * 16;
            const uint32_t yb = cb_ + Y0_REL + g * 272 + t * 4;
#pragma unroll 1
            for (int gm = 0; gm < 2; gm++) {
                float acc[8][4];
#pragma unroll
                for (int i = 0; i < 8; i++) { acc[i][0] = acc[i][1] = acc[i][2] = acc[i][3] = 0.f; }
                uint32_t a[3][4];
                const uint32_t ub0 = ua + gm * 128, ub1 = ua + gm * 144;
                auto addr = [&](int kp) { const int m0 = -2 * kp, f0 = m0 >> 4, f1 = (m0 + 8) >> 4; return (f1 != f0 ? ub1 : ub0) + (uint32_t)((m0 + f0) * 16); };
                ldsm4(addr(-3), a[0]); ldsm4(addr(-2), a[1]);
#pragma unroll
                for (int kp = -3; kp <= 16; kp++) {
                    if (kp + 2 <= 16) ldsm4(addr(kp + 2), a[(kp + 5) % 3]);
                    const uint32_t* aa = a[(kp + 3) % 3];
#pragma unroll
                    for (int d = 0; d < 8; d++) {
                        const int i = d + 2 * kp;
                        if (i >= 0 && i <= 33) mma16816(acc[d], aa[0], aa[1], aa[2], aa[3], P0[i], P1[i]);
                    }
                }
#pragma unroll
                for (int d = 0; d < 8; d++) {
                    sts32(yb + (8 * gm + d) * 16, pack_bf16(acc[d][0], acc[d][1]));
                    sts32(yb + (8 * gm + d) * 16 + 8 * 272, pack_bf16(acc[d][2], acc[d][3]));
                }
            }
            bar_arrive(6 + c, 96);
            CLK(21);
        }
        {
            mbar_wait(BAR(B_KVOK), 0);
            CLK(22);
            const float* kv = g_KV[lds32(sb + MISC_OFF) & 1];
#pragma unroll 1
            for (int jb = 0; jb < 2; jb++) {
                const int box = aw * 2 + jb;
                uint32_t kb0[4][4], zb[4][2];
                const float* kp = kv + box * 1024 + g * 16 + 2 * t;
                const float* zp = kv + 8192 + box * 64 + 2 * t;
#pragma unroll
                for (int hh = 0; hh < 4; hh++) {
#pragma unroll
                    for (int n = 0; n < 4; n++) { const float2 x = __ldcg(reinterpret_cast<const float2*>(kp + hh * 256 + (n >> 1) * 128 + (n & 1) * 8)); kb0[hh][n] = pack_bf16(x.x, x.y); }
#pragma unroll
                    for (int n = 0; n < 2; n++) { const float2 x = __ldcg(reinterpret_cast<const float2*>(zp + hh * 16 + n * 8)); zb[hh][n] = pack_bf16(x.x, x.y); }
                }
                mbar_wait(BAR(B_PQ + box), 0);
                uint32_t bx = sb + PQ_OFF + box * 8192 + ((mi & 1) * 8 + rr) * 128;
#pragma unroll 1
                for (int mm = 0; mm < 4; mm++, bx += 2048) {
                    uint32_t a[4][4];
                    float n0[4][4], n1[4][4], dn[4][4];
#pragma unroll
                    for (int hh = 0; hh < 4; hh++) ldsm4(bx + (((hh * 2 + (mi >> 1)) ^ rr) << 4), a[hh]);
#pragma unroll
                    for (int hh = 0; hh < 4; hh++) mma16816c(dn[hh], a[hh], zb[hh][0], zb[hh][1], 1e-6f);
#pragma unroll
                    for (int hh = 0; hh < 4; hh++) {
                        mma16816c(n0[hh], a[hh], kb0[hh][0], kb0[hh][1], 0.f);
                        mma16816c(n1[hh], a[hh], kb0[hh][2], kb0[hh][3], 0.f);
                    }
#pragma unroll
                    for (int hh = 0; hh < 4; hh++) {
                        const float i0 = rcpf(dn[hh][0]), i1 = rcpf(dn[hh][2]);
                        stsm4(bx + (((hh * 2 + (mi >> 1)) ^ rr) << 4), pack_bf16(n0[hh][0] * i0, n0[hh][1] * i0), pack_bf16(n0[hh][2] * i1, n0[hh][3] * i1),
                              pack_bf16(n1[hh][0] * i0, n1[hh][1] * i0), pack_bf16(n1[hh][2] * i1, n1[hh][3] * i1));
                    }
                }
            }
            fence_async_smem();
            __syncwarp();
            if (lane == 0) mbar_arrive(BAR(B_ODONE));
            CLK(23);
        }
        mbar_wait(BAR(B_YT), 0);
        CLK(24);
        transpose_inplace(sb + STG_OFF, aw, lane);
        if (lane == 0) mbar_arrive(BAR(B_YOUT));
    } else {
      asm volatile("setmaxnreg.dec.sync.aligned.u32 40;");
      if (warp == 12) {
        if (elect_one()) {
            int s = 0, ph = 0;
#pragma unroll 1
            for (int kb = 3; kb < 8; kb++) {
                mbar_wait(BAR(B_EMPTY1 + s), ph);
                const uint32_t full = BAR(B_FULL1 + s), sa = sb + s * STAGE1;
                mbar_expect_tx(full, STAGE1);
                tma2d(sa, &mX, kb * 64, mt * 128, full);
#pragma unroll 1
                for (int j = 0; j < 3; j++) tma2d(sa + XB1 + j * WB1, &mW, j * 512 + nt * 64, kb * 64, full);
                if (++s == 3) { s = 0; ph ^= 1; }
            }
            CLKL(31);
            mbar_wait(BAR(B_T1), 0);
            mbar_expect_tx(BAR(B_WO), 16384);
#pragma unroll 1
            for (int j = 0; j < 2; j++) tma2d(sb + WO_OFF + j * 8192, &mWO, (nt >> 1) * 128 + j * 64, 0, BAR(B_WO));
            mbar_wait(BAR(B_YST), 0);
#pragma unroll 1
            for (int ch = 0; ch < 4; ch++) {
                mbar_expect_tx(BAR(B_WO + 1 + ch), 2 * 14336);
#pragma unroll 1
                for (int j = 0; j < 2; j++)
                    tma2d(sb + WO2_OFF + j * WO2_HALF + ch * 14336, &mWO2, (nt >> 1) * 128 + j * 64, 64 + ch * 112, BAR(B_WO + 1 + ch));
            }
        }
      } else if (warp == 13) {
        unsigned int epoch;
        asm volatile("ld.relaxed.gpu.global.u32 %0, [%1];" : "=r"(epoch) : "l"(g_cnt) : "memory");
        epoch >>= 7;
        if (lane == 0) { sts32(sb + MISC_OFF, epoch); mbar_arrive(BAR(B_EPOCH)); }
        {
            float* other = g_KV[(epoch + 1) & 1] + blockIdx.x * 68;
            other[lane] = 0.f; other[lane + 32] = 0.f; if (lane < 4) other[lane + 64] = 0.f;
        }
        const bool leader = elect_one();
        if (leader) {
            {
                const int kx = nt, kw = mt & 7;
                const int first = kx < kw ? kx : kw;
#pragma unroll 1
                for (int ps = 0; ps < 2; ps++) {
                    const bool isx = (ps == 0) == (kx <= kw);
                    const int kb = isx ? kx : kw;
                    if (kb >= 3) {
                        while ((int)(clock() - t0) < PF_T0 + PF_DT * (kb - 3)) { }
                        if (isx) tma_prefetch2d(&mX, kb * 64, mt * 128);
                        else { tma_prefetch2d(&mW, (mt >> 3) * 512 + nt * 64, kb * 64); if (mt >= 8) tma_prefetch2d(&mW, 1024 + nt * 64, kb * 64); }
                    }
                }
                (void)first;
            }
            mbar_wait(BAR(B_GO), 0);
            mbar_expect_tx(BAR(B_UTILE), 16384);
            tma2d(sb + STG_OFF, &mU, nt * 64, mt * 128, BAR(B_UTILE));
            mbar_wait(BAR(B_UTILE), 0);
            asm volatile("cp.async.bulk.prefetch.L2.global [%0], %1;" :: "l"(reinterpret_cast<const unsigned char*>(p.wo) + blockIdx.x * 4096), "r"(4096) : "memory");
            mbar_wait(BAR(B_SOUT), 0);
#pragma unroll 1
            for (int j = 0; j < 2; j++) tma3d_store(&mUT, j * 64, mt, nt * 64, sb + STG_OFF + j * 8192);
            bulk_commit();
            bulk_wait0();
        }
        __syncwarp();
#pragma unroll 1
        for (int c = 0; c < 4; c++) { sts128(sb + U_OFF + c * U_CH + lane * 16, 0u, 0u, 0u, 0u); if (lane < 6) sts128(sb + U_OFF + c * U_CH + 512 + lane * 16, 0u, 0u, 0u, 0u); }
        __syncwarp();
        if (leader) {
            group_barrier(&g_cnt[32 * (1 + nt)], (epoch + 1) * 16);
            mbar_expect_tx(BAR(B_UT), 4 * 4352);
#pragma unroll 1
            for (int c = 0; c < 4; c++) bulk_g2s(sb + U_OFF + c * U_CH + U_PRE, g_UT + (size_t)(nt * 64 + mt * 4 + c) * 2176, 4352, BAR(B_UT));
            CLKL(25);
            mbar_wait(BAR(B_QT), 0);
#pragma unroll 1
            for (int j = 0; j < 2; j++) tma2d_store(&mQ, nt * 64, mt * 128 + j * 64, sb + QT_OFF + j * 8192);
            bulk_commit();
            bulk_wait0();
            CLKL(26);
            group_barrier(&g_cnt[32 * (17 + mt)], (epoch + 1) * 8);
            mbar_wait(BAR(B_KV), 0);
            CLKL(27);
#pragma unroll 1
            for (int j = 0; j < 8; j++) {
                mbar_expect_tx(BAR(B_PQ + j), 8192);
                tma2d(sb + PQ_OFF + j * 8192, &mQ, j * 64, (2 * mt + (nt & 1)) * 64, BAR(B_PQ + j));
            }
            mbar_wait(BAR(B_YST), 0);
            asm volatile("fence.acq_rel.gpu;" ::: "memory");
            group_barrier(&g_cnt[32 * (9 + nt)], (epoch + 1) * 16);
            CLKL(28);
            mbar_expect_tx(BAR(B_YT), 16384);
#pragma unroll 1
            for (int j = 0; j < 2; j++) tma2d(sb + STG_OFF + j * 8192, &mYT, mt * 128 + j * 64, nt * 64, BAR(B_YT));
            mbar_wait(BAR(B_YOUT), 0);
#pragma unroll 1
            for (int j = 0; j < 2; j++) tma2d_store(&mOut, nt * 64, mt * 128 + j * 64, sb + STG_OFF + j * 8192);
            bulk_commit();
            bulk_wait0_read();
            CLKL(29);
        }
      } else if (warp == 14) {
        if (elect_one()) {
            mbar_wait(BAR(B_EPOCH), 0);
            const uint32_t epoch = lds32(sb + MISC_OFF);
            mbar_wait(BAR(B_KV), 0);
            CLKL(32);
            float* kv = g_KV[epoch & 1];
            bulk_red_f32(kv + nt * 1024, sb + KVS_OFF, 4096);
            bulk_red_f32(kv + 8192 + nt * 64, sb + KVS_OFF + 4096, 256);
            bulk_commit();
            bulk_wait0();
            group_barrier(&g_cnt[0], (epoch + 1) * 128);
            mbar_arrive(BAR(B_KVOK));
            CLKL(33);
        }
      }
    }
}

typedef CUresult (*PFN_encodeTiled)(CUtensorMap*, CUtensorMapDataType, cuuint32_t, void*, const cuuint64_t*, const cuuint64_t*, const cuuint32_t*,
                                    const cuuint32_t*, CUtensorMapInterleave, CUtensorMapSwizzle, CUtensorMapL2promotion, CUtensorMapFloatOOBfill);

struct HostState {
    bool init = false;
    PFN_encodeTiled enc = nullptr;
    void *ut = nullptr, *yt = nullptr, *q = nullptr;
};

void make_map(PFN_encodeTiled enc, CUtensorMap* m, const void* base, int rank, const cuuint64_t* dims, const cuuint64_t* strides, const cuuint32_t* box) {
    const cuuint32_t es[3] = {1, 1, 1};
    enc(m, CU_TENSOR_MAP_DATA_TYPE_BFLOAT16, (cuuint32_t)rank, const_cast<void*>(base), dims, strides, box, es, CU_TENSOR_MAP_INTERLEAVE_NONE,
        CU_TENSOR_MAP_SWIZZLE_128B, CU_TENSOR_MAP_L2_PROMOTION_L2_128B, CU_TENSOR_MAP_FLOAT_OOB_FILL_NONE);
}
void make_map2(PFN_encodeTiled enc, CUtensorMap* m, const void* base, uint64_t inner, uint64_t outer, uint32_t bi, uint32_t bo) {
    const cuuint64_t dims[2] = {inner, outer}; const cuuint64_t strides[1] = {inner * 2}; const cuuint32_t box[2] = {bi, bo};
    make_map(enc, m, base, 2, dims, strides, box);
}

}

extern "C" void kernel_launch(void* const* d_in, const int* in_sizes, int n_in, void* d_out, int out_size) {
    (void)in_sizes; (void)n_in; (void)out_size;
    static HostState hs;
    if (!hs.init) {
        void* fn = nullptr; cudaDriverEntryPointQueryResult qr;
        cudaGetDriverEntryPoint("cuTensorMapEncodeTiled", &fn, cudaEnableDefault, &qr);
        hs.enc = (PFN_encodeTiled)fn;
        cudaGetSymbolAddress(&hs.ut, g_UT); cudaGetSymbolAddress(&hs.yt, g_YT); cudaGetSymbolAddress(&hs.q, g_Q);
        cudaFuncSetAttribute(fused_kernel, cudaFuncAttributeMaxDynamicSharedMemorySize, SMEM_BYTES);
        hs.init = true;
    }
    CUtensorMap mX, mW, mU, mUT, mQ, mWO, mWO2, mYT, mOut;
    make_map2(hs.enc, &mX, d_in[9], 512, 2048, 64, 128);
    make_map2(hs.enc, &mW, d_in[10], 1536, 512, 64, 64);
    make_map2(hs.enc, &mU, d_in[0], 512, 2048, 64, 128);
    {
        const cuuint64_t dims[3] = {128, 16, 512}; const cuuint64_t strides[2] = {272, 4352}; const cuuint32_t box[3] = {64, 1, 64};
        make_map(hs.enc, &mUT, hs.ut, 3, dims, strides, box);
    }
    make_map2(hs.enc, &mQ, hs.q, 512, 2048, 64, 64);
    make_map2(hs.enc, &mWO, d_in[11], 512, 512, 64, 64);
    make_map2(hs.enc, &mWO2, d_in[11], 512, 512, 64, 112);
    make_map2(hs.enc, &mYT, hs.yt, 2048, 512, 64, 64);
    make_map2(hs.enc, &mOut, d_out, 1024, 2048, 64, 64);
    Params p;
    p.A_re = (const __nv_bfloat16*)d_in[1]; p.A_im = (const __nv_bfloat16*)d_in[2];
    p.B_re = (const __nv_bfloat16*)d_in[3]; p.B_im = (const __nv_bfloat16*)d_in[4];
    p.C_re = (const __nv_bfloat16*)d_in[5]; p.C_im = (const __nv_bfloat16*)d_in[6];
    p.log_dt = (const __nv_bfloat16*)d_in[7]; p.Dskip = (const __nv_bfloat16*)d_in[8];
    p.wo = (const __nv_bfloat16*)d_in[11];
    p.zero = 0;
    fused_kernel<<<128, NTHREADS, SMEM_BYTES>>>(mX, mW, mU, mUT, mQ, mWO, mWO2, mYT, mOut, p);
}
```

```cpp
#include <cuda_runtime.h>
#include <cuda_bf16.h>
#include <cuda.h>
#include <stdint.h>

namespace {

constexpr int L_ = 2048;
constexpr int NTHREADS = 512;
constexpr int SPIN_LIMIT = 1 << 20;
#define UHOP_AT 3
#define PF_T0 1500
#define PF_DT 250
#define GO_KB 0

constexpr int STAGE1 = 40960, XB1 = 16384, WB1 = 8192;
constexpr int QT_OFF = 0, KT_OFF = 16384, VT_OFF = 32768;
constexpr int PQ_OFF = 0;
constexpr int WO_OFF = 65536;
constexpr int WO2_OFF = 81920, WO2_HALF = 57344;
constexpr int CH_BYTES = 29568;
constexpr int PARK_PITCH = 528;
constexpr int EO = 14976;
constexpr int X1E = 3680, EO1 = EO;
constexpr int X2E = X1E + 4608, EO2 = EO;
constexpr int X3E = X2E + 3328, EO3 = EO, HS3 = 1344;
constexpr int Y0_REL = X3E + 2688;
static_assert(Y0_REL + 4352 == X1E + EO && X3E + EO + 2688 <= 29568, "channel region");
constexpr int CH012_OFF = 122880, CH3_OFF = 81920;
constexpr int U_OFF = CH012_OFF + 3 * CH_BYTES;
constexpr int U_CH = 4960, U_PRE = 608;
constexpr int KVS_OFF = 111616;
constexpr int STG_OFF = 211968;
constexpr int BAR_OFF = 231424;
constexpr int MISC_OFF = BAR_OFF + 400;
constexpr int CLK_OFF = MISC_OFF + 192;
constexpr int SMEM_BYTES = 232448;
static_assert(U_OFF + 4 * U_CH <= BAR_OFF && STG_OFF + 16384 <= BAR_OFF && STG_OFF >= U_OFF, "u region");

enum { B_FULL1 = 0, B_GO = 3, B_UTILE = 4, B_UT = 5, B_EPOCH = 6, B_KVOK = 7, B_YT = 8, B_TAPS = 9, B_PQ = 13, B_WO = 21, B_YRDY = 26, B_KM = 27,
       B_EMPTY1 = 31, B_S2FREE = 34, B_SOUT = 35, B_ODONE = 36, B_YOUT = 37, B_T1 = 38, B_QT = 39, B_KV = 40, B_YST = 41, B_CONV = 42, B_COUNT = 43 };

__device__ __nv_bfloat16 g_UT[512 * 2176];
__device__ __nv_bfloat16 g_YT[512 * 2048];
__device__ __nv_bfloat16 g_Q[2048 * 512];
__device__ float g_KV[2][32 * 256 + 512];
__device__ unsigned int g_cnt[32 * 40];
#define CLK(i) do { } while (0)
#define CLKL(i) do { } while (0)
#define GTM(i) do { } while (0)

struct Params {
    const __nv_bfloat16 *A_re, *A_im, *B_re, *B_im, *C_re, *C_im, *log_dt, *Dskip, *wo;
    int zero;
};

__device__ __forceinline__ uint32_t smem_u32(const void* p) { return (uint32_t)__cvta_generic_to_shared(p); }
__device__ __forceinline__ bool elect_one() { uint32_t p; asm volatile("{\n.reg .pred P;\nelect.sync _|P, 0xffffffff;\nselp.u32 %0, 1, 0, P;\n}" : "=r"(p)); return p != 0; }
__device__ __forceinline__ void mbar_init(uint32_t bar, uint32_t cnt) { asm volatile("mbarrier.init.shared::cta.b64 [%0], %1;" :: "r"(bar), "r"(cnt) : "memory"); }
__device__ __forceinline__ void mbar_expect_tx(uint32_t bar, uint32_t bytes) { asm volatile("mbarrier.arrive.expect_tx.shared::cta.b64 _, [%0], %1;" :: "r"(bar), "r"(bytes) : "memory"); }
__device__ __forceinline__ void mbar_arrive(uint32_t bar) { asm volatile("mbarrier.arrive.shared::cta.b64 _, [%0];" :: "r"(bar) : "memory"); }
__device__ __forceinline__ void mbar_wait(uint32_t bar, uint32_t parity) {
    asm volatile("{\n.reg .pred p;\n.reg .u32 n;\nmov.u32 n, %2;\nWL_%=:\nmbarrier.try_wait.parity.shared::cta.b64 p, [%0], %1;\n@p bra WD_%=;\n"
                 "sub.u32 n, n, 1;\nsetp.ne.u32 p, n, 0;\n@p bra WL_%=;\nWD_%=:\n}" :: "r"(bar), "r"(parity), "n"(SPIN_LIMIT) : "memory");
}
__device__ __forceinline__ void tma2d(uint32_t dst, const CUtensorMap* map, int c0, int c1, uint32_t bar) {
    asm volatile("cp.async.bulk.tensor.2d.shared::cluster.global.mbarrier::complete_tx::bytes [%0], [%1, {%3, %4}], [%2];"
        :: "r"(dst), "l"(map), "r"(bar), "r"(c0), "r"(c1) : "memory");
}
__device__ __forceinline__ void bulk_g2s(uint32_t dst, const void* src, uint32_t bytes, uint32_t bar) {
    asm volatile("cp.async.bulk.shared::cluster.global.mbarrier::complete_tx::bytes [%0], [%1], %2, [%3];" :: "r"(dst), "l"(src), "r"(bytes), "r"(bar) : "memory");
}
__device__ __forceinline__ void tma2d_store(const CUtensorMap* map, int c0, int c1, uint32_t src) {
    asm volatile("cp.async.bulk.tensor.2d.global.shared::cta.bulk_group [%0, {%2, %3}], [%1];" :: "l"(map), "r"(src), "r"(c0), "r"(c1) : "memory");
}
__device__ __forceinline__ void tma3d_store(const CUtensorMap* map, int c0, int c1, int c2, uint32_t src) {
    asm volatile("cp.async.bulk.tensor.3d.global.shared::cta.bulk_group [%0, {%2, %3, %4}], [%1];" :: "l"(map), "r"(src), "r"(c0), "r"(c1), "r"(c2) : "memory");
}
__device__ __forceinline__ void tma_prefetch2d(const CUtensorMap* map, int c0, int c1) {
    asm volatile("cp.async.bulk.prefetch.tensor.2d.L2.global.tile [%0, {%1, %2}];" :: "l"(map), "r"(c0), "r"(c1) : "memory");
}
__device__ __forceinline__ void bulk_commit() { asm volatile("cp.async.bulk.commit_group;" ::: "memory"); }
__device__ __forceinline__ void bulk_wait0() { asm volatile("cp.async.bulk.wait_group 0;" ::: "memory"); }
__device__ __forceinline__ void bulk_wait0_read() { asm volatile("cp.async.bulk.wait_group.read 0;" ::: "memory"); }
__device__ __forceinline__ void fence_async_smem() { asm volatile("fence.proxy.async.shared::cta;" ::: "memory"); }
__device__ __forceinline__ void fence_async_global() { asm volatile("fence.proxy.async.global;" ::: "memory"); }
__device__ __forceinline__ void bar_sync(int id, int n) { asm volatile("bar.sync %0, %1;" :: "r"(id), "r"(n) : "memory"); }
__device__ __forceinline__ void bar_arrive(int id, int n) { asm volatile("bar.arrive %0, %1;" :: "r"(id), "r"(n) : "memory"); }
__device__ __forceinline__ void group_barrier(unsigned int* p, unsigned int target) {
    asm volatile("fence.proxy.async.global;\nred.relaxed.gpu.global.add.u32 [%0], 1;" :: "l"(p) : "memory");
    asm volatile("{\n.reg .pred p;\n.reg .u32 n, v;\nmov.u32 n, %2;\nPL_%=:\nld.relaxed.gpu.global.u32 v, [%0];\nsub.u32 v, v, %1;\nsetp.ge.s32 p, v, 0;\n@p bra PD_%=;\n"
                 "sub.u32 n, n, 1;\nsetp.ne.u32 p, n, 0;\n@p bra PL_%=;\nPD_%=:\n"
                 "ld.acquire.gpu.global.u32 v, [%0];\n"
                 "fence.proxy.async.global;\n}" :: "l"(p), "r"(target), "n"(SPIN_LIMIT) : "memory");
}
__device__ __forceinline__ void bulk_s2g(void* dst, uint32_t src, uint32_t bytes) {
    asm volatile("cp.async.bulk.global.shared::cta.bulk_group [%0], [%1], %2;" :: "l"(dst), "r"(src), "r"(bytes) : "memory");
}
__device__ __forceinline__ void bulk_red_f32(void* dst, uint32_t src, uint32_t bytes) {
    asm volatile("cp.reduce.async.bulk.global.shared::cta.bulk_group.add.f32 [%0], [%1], %2;" :: "l"(dst), "r"(src), "r"(bytes) : "memory");
}
__device__ __forceinline__ void wg_fence() { asm volatile("wgmma.fence.sync.aligned;" ::: "memory"); }
__device__ __forceinline__ void wg_commit() { asm volatile("wgmma.commit_group.sync.aligned;" ::: "memory"); }
template <int N> __device__ __forceinline__ void wg_wait() { asm volatile("wgmma.wait_group.sync.aligned %0;" :: "n"(N) : "memory"); }
__device__ __forceinline__ uint64_t mkdesc(uint32_t saddr, uint32_t lbo) {
    return (uint64_t)((saddr & 0x3FFFF) >> 4) | ((uint64_t)(lbo >> 4) << 16) | ((uint64_t)(1024 >> 4) << 32) | ((uint64_t)1 << 62);
}
#define R4(b) "+f"(d[b]), "+f"(d[b + 1]), "+f"(d[b + 2]), "+f"(d[b + 3])
#define R16(b) R4(b), R4(b + 4), R4(b + 8), R4(b + 12)
__device__ __forceinline__ void wgmma192(float* d, uint64_t da, uint64_t db, int scale_d) {
    asm volatile("{\n.reg .pred p;\nsetp.ne.b32 p, %98, 0;\n"
        "wgmma.mma_async.sync.aligned.m64n192k16.f32.bf16.bf16 {"
        "%0,%1,%2,%3,%4,%5,%6,%7,%8,%9,%10,%11,%12,%13,%14,%15,%16,%17,%18,%19,%20,%21,%22,%23,%24,%25,%26,%27,%28,%29,%30,%31,"
        "%32,%33,%34,%35,%36,%37,%38,%39,%40,%41,%42,%43,%44,%45,%46,%47,%48,%49,%50,%51,%52,%53,%54,%55,%56,%57,%58,%59,%60,%61,%62,%63,"
        "%64,%65,%66,%67,%68,%69,%70,%71,%72,%73,%74,%75,%76,%77,%78,%79,%80,%81,%82,%83,%84,%85,%86,%87,%88,%89,%90,%91,%92,%93,%94,%95"
        "}, %96, %97, p, 1, 1, 0, 1;\n}\n"
        : R16(0), R16(16), R16(32), R16(48), R16(64), R16(80) : "l"(da), "l"(db), "r"(scale_d));
}
__device__ __forceinline__ void wgmma64(float* d, uint64_t da, uint64_t db, int scale_d) {
    asm volatile("{\n.reg .pred p;\nsetp.ne.b32 p, %34, 0;\n"
        "wgmma.mma_async.sync.aligned.m64n64k16.f32.bf16.bf16 {"
        "%0,%1,%2,%3,%4,%5,%6,%7,%8,%9,%10,%11,%12,%13,%14,%15,%16,%17,%18,%19,%20,%21,%22,%23,%24,%25,%26,%27,%28,%29,%30,%31"
        "}, %32, %33, p, 1, 1, 0, 1;\n}\n"
        : R16(0), R16(16) : "l"(da), "l"(db), "r"(scale_d));
}
__device__ __forceinline__ void wgmma128(float* d, uint64_t da, uint64_t db, int scale_d) {
    asm volatile("{\n.reg .pred p;\nsetp.ne.b32 p, %66, 0;\n"
        "wgmma.mma_async.sync.aligned.m64n128k16.f32.bf16.bf16 {"
        "%0,%1,%2,%3,%4,%5,%6,%7,%8,%9,%10,%11,%12,%13,%14,%15,%16,%17,%18,%19,%20,%21,%22,%23,%24,%25,%26,%27,%28,%29,%30,%31,"
        "%32,%33,%34,%35,%36,%37,%38,%39,%40,%41,%42,%43,%44,%45,%46,%47,%48,%49,%50,%51,%52,%53,%54,%55,%56,%57,%58,%59,%60,%61,%62,%63"
        "}, %64, %65, p, 1, 1, 0, 1;\n}\n"
        : R16(0), R16(16), R16(32), R16(48) : "l"(da), "l"(db), "r"(scale_d));
}
__device__ __forceinline__ void mma16816(float* d, uint32_t a0, uint32_t a1, uint32_t a2, uint32_t a3, uint32_t b0, uint32_t b1) {
    asm volatile("mma.sync.aligned.m16n8k16.row.col.f32.bf16.bf16.f32 {%0,%1,%2,%3}, {%4,%5,%6,%7}, {%8,%9}, {%0,%1,%2,%3};"
        : "+f"(d[0]), "+f"(d[1]), "+f"(d[2]), "+f"(d[3]) : "r"(a0), "r"(a1), "r"(a2), "r"(a3), "r"(b0), "r"(b1));
}
__device__ __forceinline__ void mma16816c(float* d, const uint32_t* a, uint32_t b0, uint32_t b1, float c) {
    asm volatile("mma.sync.aligned.m16n8k16.row.col.f32.bf16.bf16.f32 {%0,%1,%2,%3}, {%4,%5,%6,%7}, {%8,%9}, {%10,%10,%10,%10};"
        : "=f"(d[0]), "=f"(d[1]), "=f"(d[2]), "=f"(d[3]) : "r"(a[0]), "r"(a[1]), "r"(a[2]), "r"(a[3]), "r"(b0), "r"(b1), "f"(c));
}
__device__ __forceinline__ void ldsm4(uint32_t addr, uint32_t* r) {
    asm volatile("ldmatrix.sync.aligned.m8n8.x4.shared.b16 {%0,%1,%2,%3}, [%4];" : "=r"(r[0]), "=r"(r[1]), "=r"(r[2]), "=r"(r[3]) : "r"(addr) : "memory");
}
__device__ __forceinline__ void ldsm4t(uint32_t addr, uint32_t* r) {
    asm volatile("ldmatrix.sync.aligned.m8n8.x4.trans.shared.b16 {%0,%1,%2,%3}, [%4];" : "=r"(r[0]), "=r"(r[1]), "=r"(r[2]), "=r"(r[3]) : "r"(addr) : "memory");
}
__device__ __forceinline__ void stsm4(uint32_t addr, uint32_t r0, uint32_t r1, uint32_t r2, uint32_t r3) {
    asm volatile("stmatrix.sync.aligned.m8n8.x4.shared.b16 [%0], {%1,%2,%3,%4};" :: "r"(addr), "r"(r0), "r"(r1), "r"(r2), "r"(r3) : "memory");
}
__device__ __forceinline__ uint32_t pack_bf16(float lo, float hi) { uint32_t r; asm("cvt.rn.bf16x2.f32 %0, %1, %2;" : "=r"(r) : "f"(hi), "f"(lo)); return r; }
__device__ __forceinline__ uint32_t hadd2(uint32_t a, uint32_t b) { uint32_t r; asm("add.rn.bf16x2 %0, %1, %2;" : "=r"(r) : "r"(a), "r"(b)); return r; }
__device__ __forceinline__ float bf_lo(uint32_t v) { return __uint_as_float(v << 16); }
__device__ __forceinline__ float bf_hi(uint32_t v) { return __uint_as_float(v & 0xffff0000u); }
__device__ __forceinline__ uint32_t lds32(uint32_t a) { uint32_t v; asm volatile("ld.shared.b32 %0, [%1];" : "=r"(v) : "r"(a) : "memory"); return v; }
__device__ __forceinline__ void lds128(uint32_t a, uint32_t* r) { asm volatile("ld.shared.v4.b32 {%0,%1,%2,%3}, [%4];" : "=r"(r[0]), "=r"(r[1]), "=r"(r[2]), "=r"(r[3]) : "r"(a) : "memory"); }
__device__ __forceinline__ void lds128v(uint32_t a, uint32_t* r) { asm volatile("ld.volatile.shared.v4.b32 {%0,%1,%2,%3}, [%4];" : "=r"(r[0]), "=r"(r[1]), "=r"(r[2]), "=r"(r[3]) : "r"(a) : "memory"); }
__device__ __forceinline__ uint32_t lds32v(uint32_t a) { uint32_t v; asm volatile("ld.volatile.shared.b32 %0, [%1];" : "=r"(v) : "r"(a) : "memory"); return v; }
__device__ __forceinline__ void lds128f(uint32_t a, float* r) { asm volatile("ld.shared.v4.f32 {%0,%1,%2,%3}, [%4];" : "=f"(r[0]), "=f"(r[1]), "=f"(r[2]), "=f"(r[3]) : "r"(a) : "memory"); }
__device__ __forceinline__ void sts16(uint32_t a, uint32_t v) { asm volatile("st.shared.b16 [%0], %1;" :: "r"(a), "h"((unsigned short)v) : "memory"); }
__device__ __forceinline__ void sts32(uint32_t a, uint32_t v) { asm volatile("st.shared.b32 [%0], %1;" :: "r"(a), "r"(v) : "memory"); }
__device__ __forceinline__ void sts64(uint32_t a, uint32_t x, uint32_t y) { asm volatile("st.shared.v2.b32 [%0], {%1,%2};" :: "r"(a), "r"(x), "r"(y) : "memory"); }
__device__ __forceinline__ void sts64f(uint32_t a, float x, float y) { asm volatile("st.shared.v2.f32 [%0], {%1,%2};" :: "r"(a), "f"(x), "f"(y) : "memory"); }
__device__ __forceinline__ void sts128(uint32_t a, uint32_t x, uint32_t y, uint32_t z, uint32_t w) { asm volatile("st.shared.v4.b32 [%0], {%1,%2,%3,%4};" :: "r"(a), "r"(x), "r"(y), "r"(z), "r"(w) : "memory"); }
__device__ __forceinline__ float ex2f(float x) { float y; asm("ex2.approx.ftz.f32 %0, %1;" : "=f"(y) : "f"(x)); return y; }
__device__ __forceinline__ float rcpf(float x) { float y; asm("rcp.approx.ftz.f32 %0, %1;" : "=f"(y) : "f"(x)); return y; }
__device__ __forceinline__ float phi_fn(float x) {
    const float th = x * 0.7213475204444817f;
    return fmaf(x, 0.5f, fmaf(fabsf(x), 0.5f, 1e-6f)) + ex2f(th - fabsf(th));
}
__device__ __forceinline__ uint32_t bf16_bits(float x) { return pack_bf16(x, 0.f); }
__device__ __forceinline__ float bf16_round(float x) { return bf_lo(pack_bf16(x, 0.f)); }

struct C2 { float r, i; };
__device__ __forceinline__ C2 cmul(C2 a, C2 b) { C2 o; o.r = fmaf(a.r, b.r, -(a.i * b.i)); o.i = fmaf(a.r, b.i, a.i * b.r); return o; }
__device__ __forceinline__ C2 csq(C2 a) { C2 o; o.r = fmaf(a.r, a.r, -(a.i * a.i)); o.i = (a.r + a.r) * a.i; return o; }
__device__ __forceinline__ C2 cexp_t(float sg2, float wt, float t) {
    const float m = ex2f(sg2 * t);
    float r = wt * t; r -= rintf(r);
    const float a = r * 6.283185307179586f;
    C2 o; o.r = m * __cosf(a); o.i = m * __sinf(a); return o;
}
__device__ __forceinline__ void transpose_inplace(uint32_t base, int aw, int lane) {
    const int mi = lane >> 3, rr = lane & 7;
    const int srow = aw * 16 + (mi & 1) * 8 + rr;
    uint32_t v[8][4];
#pragma unroll
    for (int i = 0; i < 8; i++) ldsm4t(base + (i >> 2) * 8192 + srow * 128 + ((((i & 3) * 2 + (mi >> 1)) ^ rr) << 4), v[i]);
    bar_sync(12, 128);
    const uint32_t d = base + ((mi >> 1) * 8 + rr) * 128 + (((aw * 2 + (mi & 1)) ^ rr) << 4);
#pragma unroll
    for (int i = 0; i < 8; i++) stsm4(d + (i >> 2) * 8192 + (i & 3) * 2048, v[i][0], v[i][1], v[i][2], v[i][3]);
    fence_async_smem();
    __syncwarp();
}
__device__ __forceinline__ uint32_t u_chunk(uint32_t ub, int chi) { return ub + U_PRE + (chi + (chi >> 4)) * 16; }

template <int NTILE, int BMIN, int NSET>
__device__ __forceinline__ void conv_octave(uint32_t fq, uint32_t xa, uint32_t ya, uint32_t set_stride) {
    uint32_t Qe[5][4], Qo[5][4];
    {
        uint32_t Fe[11], Fo[11];
#pragma unroll
        for (int i = 0; i < 11; i++) { Fe[i] = lds32(fq - 16 * i); Fo[i] = lds32(fq + 416 - 16 * i); }
#pragma unroll
        for (int k = 0; k < 5; k++) {
            Qe[k][0] = Fe[2 * k + 1]; Qe[k][1] = Fe[2 * k + 2]; Qe[k][2] = Fe[2 * k]; Qe[k][3] = Fe[2 * k + 1];
            Qo[k][0] = Fo[2 * k + 1]; Qo[k][1] = Fo[2 * k + 2]; Qo[k][2] = Fo[2 * k]; Qo[k][3] = Fo[2 * k + 1];
#pragma unroll
            for (int i = 0; i < 4; i++) { asm volatile("mov.b32 %0, %0;" : "+r"(Qe[k][i])); asm volatile("mov.b32 %0, %0;" : "+r"(Qo[k][i])); }
        }
    }
    float acc[NSET][NTILE][4];
#pragma unroll
    for (int n = 0; n < NSET; n++)
#pragma unroll
        for (int i = 0; i < NTILE; i++) { acc[n][i][0] = acc[n][i][1] = acc[n][i][2] = acc[n][i][3] = 0.f; }
    uint32_t b[NSET][3][4];
#pragma unroll
    for (int n = 0; n < NSET; n++) { ldsm4t(xa + n * set_stride + BMIN * 256, b[n][BMIN % 3]); ldsm4t(xa + n * set_stride + (BMIN + 1) * 256, b[n][(BMIN + 1) % 3]); }
#pragma unroll
    for (int be = BMIN; be < NTILE + 4; be++) {
#pragma unroll
        for (int n = 0; n < NSET; n++) {
            if (be + 2 < NTILE + 4) ldsm4t(xa + n * set_stride + (be + 2) * 256, b[n][(be + 2) % 3]);
            if (BMIN == 0 || be > BMIN || n == NSET - 1) {
#pragma unroll
                for (int k = 0; k < 5; k++) { const int tl = be - 4 + k; if (tl >= 0 && tl < NTILE) mma16816(acc[n][tl], Qe[k][0], Qe[k][1], Qe[k][2], Qe[k][3], b[n][be % 3][0], b[n][be % 3][1]); }
            }
        }
        if (BMIN == 0 || be > BMIN) {
#pragma unroll
            for (int n = 0; n < NSET; n++)
#pragma unroll
                for (int k = 0; k < 5; k++) { const int tl = be - 4 + k; if (tl >= 0 && tl < NTILE) mma16816(acc[n][tl], Qo[k][0], Qo[k][1], Qo[k][2], Qo[k][3], b[n][be % 3][2], b[n][be % 3][3]); }
        }
        if (be >= 5) {
#pragma unroll
            for (int n = 0; n < NSET; n++) { const float* a = acc[n][be - 5]; sts32(ya + n * set_stride + (be - 1) * 256, pack_bf16(a[0], a[1])); sts32(ya + n * set_stride + (be - 1) * 256 + 128, pack_bf16(a[2], a[3])); }
        }
    }
#pragma unroll
    for (int n = 0; n < NSET; n++) { const float* a = acc[n][NTILE - 1]; sts32(ya + n * set_stride + (NTILE + 3) * 256, pack_bf16(a[0], a[1])); sts32(ya + n * set_stride + (NTILE + 3) * 256 + 128, pack_bf16(a[2], a[3])); }
}

__global__ void __launch_bounds__(NTHREADS, 1)
fused_kernel(const __grid_constant__ CUtensorMap mX, const __grid_constant__ CUtensorMap mW, const __grid_constant__ CUtensorMap mU,
             const __grid_constant__ CUtensorMap mUT, const __grid_constant__ CUtensorMap mQ, const __grid_constant__ CUtensorMap mWO,
             const __grid_constant__ CUtensorMap mWO2, const __grid_constant__ CUtensorMap mYT, const __grid_constant__ CUtensorMap mOut, const Params p) {
    extern __shared__ __align__(1024) unsigned char smem_raw[];
    const uint32_t sb = smem_u32(smem_raw);
    const int lane = threadIdx.x & 31, hwarp = __shfl_sync(0xffffffffu, threadIdx.x >> 5, 0);
    const int warp = hwarp;
    const int g = lane >> 2, t = lane & 3, mi = lane >> 3, rr = lane & 7;
    const int mt = blockIdx.x & 15, nt = blockIdx.x >> 4;
    const uint32_t bars = sb + BAR_OFF;
    const uint32_t t0 = clock();
#define BAR(i) (bars + (i) * 8)

    if (warp == 12) {
        const bool leader = elect_one();
        if (leader) {
            mbar_init(BAR(B_FULL1), 1); mbar_init(BAR(B_FULL1 + 1), 1); mbar_init(BAR(B_FULL1 + 2), 1);
            asm volatile("fence.mbarrier_init.release.cluster;" ::: "memory");
        }
        __syncwarp();
        bar_arrive(0, NTHREADS);
        if (leader) {
#pragma unroll 1
            for (int kb = 0; kb < 3; kb++) {
                const uint32_t full = BAR(B_FULL1 + kb), sa = sb + kb * STAGE1;
                mbar_expect_tx(full, STAGE1);
                tma2d(sa, &mX, kb * 64, mt * 128, full);
#pragma unroll 1
                for (int j = 0; j < 3; j++) tma2d(sa + XB1 + j * WB1, &mW, j * 512 + nt * 64, kb * 64, full);
            }
            CLKL(30);
        }
        __syncwarp();
        bar_sync(13, 64);
    } else {
        if (warp < 12 && elect_one()) {
#pragma unroll 1
            for (int i = 3 + 4 * warp; i < min(7 + 4 * warp, (int)B_COUNT); i++) mbar_init(BAR(i), i < B_EMPTY1 ? 1 : (i < B_SOUT ? 2 : (i < B_T1 ? 4 : 8)));
            asm volatile("fence.mbarrier_init.release.cluster;" ::: "memory");
        }
        __syncwarp();
        bar_sync(0, NTHREADS);
        if (warp == 13) bar_arrive(13, 64);
    }

    if (warp < 8) {
        asm volatile("setmaxnreg.inc.sync.aligned.u32 160;");
        const int wg = warp >> 2, w4 = warp & 3;
        const uint32_t wrow = sb + (wg * 64 + w4 * 16) * 128;
        const uint32_t frow = (uint32_t)(((mi & 1) * 8 + rr) * 128);
        {
            float acc[96];
            int s = 0, ph = 0;
#pragma unroll 1
            for (int kb = 0; kb < 8; kb++) {
                mbar_wait(BAR(B_FULL1 + s), ph);
                if (kb == GO_KB && warp == 0 && lane == 0) mbar_arrive(BAR(B_GO));

                const uint64_t da = mkdesc(sb + s * STAGE1 + wg * (XB1 / 2), 16), db = mkdesc(sb + s * STAGE1 + XB1, WB1);
                wg_fence();
#pragma unroll
                for (int j = 0; j < 4; j++) wgmma192(acc, da + j * 2, db + j * 128, (kb | j) ? 1 : 0);
                wg_commit();
                if (kb > 0) {
                    wg_wait<1>();
                    if (kb <= 6 && w4 == 0 && lane == 0) mbar_arrive(BAR(kb == 6 ? B_S2FREE : B_EMPTY1 + (s == 0 ? 2 : s - 1)));
                }
                if (++s == 3) { s = 0; ph ^= 1; }
            }
            wg_wait<0>();
            CLK(1 + wg);
            if (warp == 0) GTM(38);
            if (lane == 0) mbar_arrive(BAR(B_T1));
            bar_sync(1, 256);
#pragma unroll
            for (int jj = 0; jj < 12; jj++) {
                const int j = jj < 8 ? jj + 4 : jj - 8;
                const int a = j * 8;
                float v[8];
#pragma unroll
                for (int i = 0; i < 8; i++) v[i] = j < 8 ? phi_fn(acc[a + i]) : acc[a + i];
                stsm4(wrow + frow + (j >> 2) * 16384 + ((((j & 3) * 2 + (mi >> 1)) ^ rr) << 4), pack_bf16(v[0], v[1]), pack_bf16(v[2], v[3]),
                      pack_bf16(v[4], v[5]), pack_bf16(v[6], v[7]));
                if (j < 8 && p.zero) asm volatile("trap;");
            }
                        fence_async_smem(); __syncwarp();
            if (lane == 0) mbar_arrive(BAR(B_QT));
                    }
        bar_sync(1, 256);
        {
            const int hh = warp >> 1, dh = warp & 1;
            float ckv[2][4], cz[2][4];
#pragma unroll
            for (int i = 0; i < 4; i++) { ckv[0][i] = ckv[1][i] = cz[0][i] = cz[1][i] = 0.f; }
            const uint32_t ones = 0x3f803f80u;
            const uint32_t av = sb + VT_OFF + ((mi >> 1) * 8 + rr) * 128 + (((hh * 2 + (mi & 1)) ^ rr) << 4);
            const uint32_t ak = sb + KT_OFF + (mi * 8 + rr) * 128 + (((hh * 2 + dh) ^ rr) << 4);
            uint32_t fa[8][4], fb[4][4];
#pragma unroll
            for (int ks = 0; ks < 4; ks++) { ldsm4t(ak + ks * 4096, fb[ks]); ldsm4t(av + ks * 4096, fa[2 * ks]); ldsm4t(av + ks * 4096 + 2048, fa[2 * ks + 1]); }
#pragma unroll
            for (int ks = 0; ks < 4; ks++) {
                mma16816(ckv[0], fa[2 * ks][0], fa[2 * ks][1], fa[2 * ks][2], fa[2 * ks][3], fb[ks][0], fb[ks][1]);
                mma16816(ckv[1], fa[2 * ks + 1][0], fa[2 * ks + 1][1], fa[2 * ks + 1][2], fa[2 * ks + 1][3], fb[ks][2], fb[ks][3]);
                mma16816(cz[0], ones, ones, ones, ones, fb[ks][0], fb[ks][1]);
                mma16816(cz[1], ones, ones, ones, ones, fb[ks][2], fb[ks][3]);
            }
            const uint32_t ks_ = sb + KVS_OFF + hh * 1024 + lane * 16 + dh * 8;
            sts64f(ks_, ckv[0][0] + ckv[1][0], ckv[0][1] + ckv[1][1]);
            sts64f(ks_ + 512, ckv[0][2] + ckv[1][2], ckv[0][3] + ckv[1][3]);
            if (g == 0) sts64f(sb + KVS_OFF + 4096 + hh * 64 + t * 16 + dh * 8, cz[0][0] + cz[1][0], cz[0][1] + cz[1][1]);
            fence_async_smem();
            __syncwarp();
            if (lane == 0) mbar_arrive(BAR(B_KV));
            CLK(3 + wg);
        }
        const int c = w4;
        const uint32_t ub = sb + U_OFF + c * U_CH, cb_ = sb + (c < 3 ? CH012_OFF + c * CH_BYTES : CH3_OFF);
        mbar_wait(BAR(B_KM + c), 0);
        mbar_wait(BAR(B_UT), 0);
        int chi = wg * 32 - 32 + lane;
        uint32_t ul[4];
#pragma unroll
        for (int q = 0; q < 4; q++) ul[q] = u_chunk(ub, chi - 2 + q);
        const uint32_t x1s = (lane & 4) * 4;
        uint32_t a3 = cb_ + X3E + (chi & 1) * HS3 + ((chi >> 1) + 16) * 16, a2 = cb_ + X2E + (chi + 16) * 16, a1 = cb_ + X1E + (2 * chi + 64) * 16;
        uint32_t rn[16];
#pragma unroll
        for (int q = 0; q < 4; q++) { lds128v(ul[q], rn + 4 * q); ul[q] += 1088; }
#pragma unroll 1
        for (int it = 0; it < 4; it++, chi += 64, a3 += 512, a2 += 1024, a1 += 2048) {
            const int chi0 = it * 64 + wg * 32 - 32;
            uint32_t r[16];
#pragma unroll
            for (int i = 0; i < 16; i++) r[i] = rn[i];
            if (it < 3) {
#pragma unroll
                for (int q = 0; q < 4; q++) { lds128v(ul[q], rn + 4 * q); ul[q] += 1088; }
            }
            uint32_t sh[13], w2[12], w4[12], e4[4], o4[4];
#pragma unroll
            for (int k = 2; k <= 12; k++) sh[k] = __byte_perm(r[k], r[k + 1], 0x5432);
#pragma unroll
            for (int p = 6; p < 12; p++) w2[p] = hadd2(hadd2(sh[p - 1], sh[p]), r[p]);
            if (chi0 < 192) {
#pragma unroll
                for (int p = 8; p < 12; p++) w4[p] = hadd2(w2[p], hadd2(r[p - 1], r[p + 1]));
                if (chi0 < 128) {
#pragma unroll
                    for (int p = 4; p < 8; p++) {
                        const uint32_t w2p = p < 6 ? hadd2(hadd2(sh[p - 1], sh[p]), r[p]) : w2[p];
                        o4[p - 4] = hadd2(hadd2(w2p, hadd2(r[p - 1], r[p + 1])), hadd2(sh[p - 2], sh[p + 1]));
                        e4[p - 4] = hadd2(hadd2(w4[p + 4], hadd2(sh[p + 2], sh[p + 5])), hadd2(r[p + 2], r[p + 6]));
                    }
                    sts128(a3, e4[0], e4[1], e4[2], e4[3]);
                    sts128(a3 + EO3, o4[0], o4[1], o4[2], o4[3]);
                }
                if (chi >= -16) {
                    sts128(a2, w4[8], w4[9], w4[10], w4[11]);
                    sts128(a2 + EO2, w2[6], w2[7], w2[8], w2[9]);
                }
            }
#pragma unroll
            for (int h = 0; h < 2; h++) {
                if (h == 0 ? chi < 112 : chi >= 80) {
                    const uint32_t a = a1 + (h ? 8 - 3584 : 0) + x1s, b = a1 + (h ? 8 - 3584 : 0) + 16 - x1s;
                    sts64(a, w2[8], w2[9]); sts64(b, w2[10], w2[11]);
                    sts64(a + EO1, r[7], r[8]); sts64(b + EO1, r[9], r[10]);
                }
            }
        }
        bar_sync(2 + c, 64);
        mbar_wait(BAR(B_TAPS + c), 0);
        CLK(5 + wg);
        {
            const uint32_t fq = cb_ + 1184 + (uint32_t)((g & 1) * 208 + (t - (g >> 1)) * 4) + 44 * 4;
            const uint32_t xl = ((mi & 1) * 8 + rr) * 16, yl = g * 16 + t * 4;
            if (wg == 0) conv_octave<14, 0, 1>(fq, cb_ + X1E + (mi >> 1) * EO1 + (xl ^ ((mi & 1) * 16)), cb_ + X1E + (t >> 1) * 64 + g * 8 + (t & 1) * 4, 0);
            else {
                conv_octave<12, 3, 1>(fq + 832, cb_ + X2E - 768 + (mi >> 1) * EO2 + xl, cb_ + X2E - 768 + yl, 0);
                conv_octave<4, 3, 2>(fq + 1664, cb_ + X3E - 768 + (mi >> 1) * EO3 + xl, cb_ + X3E - 768 + yl, HS3);
            }
        }
        CLK(7 + wg);
        if (lane == 0) mbar_arrive(BAR(B_CONV));
        bar_sync(6 + c, 96);
        {
            const float g256 = __uint_as_float(lds32(sb + MISC_OFF + 128 + c * 16)), g512 = __uint_as_float(lds32(sb + MISC_OFF + 128 + c * 16 + 4)),
                        g1024 = __uint_as_float(lds32(sb + MISC_OFF + 128 + c * 16 + 8));
            const uint32_t u01 = lds32(ub + U_PRE), u23 = lds32(ub + U_PRE + 4);
            const float s0 = bf_lo(u01), s1 = s0 + bf_hi(u01), s2 = s1 + bf_lo(u23), s3 = s2 + bf_hi(u23);
            const int tau = wg * 32 + lane;
            const uint32_t a0 = cb_ + Y0_REL + (tau + (tau >> 4)) * 16;
            const uint32_t a2 = cb_ + X2E + 256 + (tau - 64) * 16;
            const uint32_t a3 = cb_ + X3E + 256 + (tau & 1) * HS3 + ((tau - 128) >> 1) * 16;
            const uint32_t ac = u_chunk(ub, tau - 128), ad = u_chunk(ub, tau - 127);
            const uint32_t ay = cb_ + (c == 0 ? 0 : X1E + EO) + tau * 16;
            uint32_t y0[4][4], y1[4][4], y2[4][4], y3[4][4], pq[4][8];
#pragma unroll
            for (int it = 0; it < 4; it++) {
                const int ta = tau + 64 * it;
                lds128(a0 + 1088 * it, y0[it]);
                if (it >= 1 || wg) {
                    const int h = ta >= 144, r = ta - 32 - 112 * h;
                    lds128(cb_ + X1E + 1024 + (r >> 3) * 256 + ((r >> 2) & 1) * 128 + h * 64 + (r & 3) * 16, y1[it]);
                }
                if (it >= 1) lds128(a2 + 1024 * it, y2[it]);
                if (it >= 2) lds128(a3 + 512 * it, y3[it]);
                if (it >= 2 || (it == 1 && wg)) { lds128(ac + 1088 * it, pq[it]); lds128(ad + 1088 * it, pq[it] + 4); }
            }
#pragma unroll
            for (int it = 0; it < 4; it++) {
                const int ta = tau + 64 * it;
                float v[8];
#pragma unroll
                for (int i = 0; i < 4; i++) { v[2 * i] = bf_lo(y0[it][i]); v[2 * i + 1] = bf_hi(y0[it][i]); }
                if (it >= 1 || wg) {
#pragma unroll
                    for (int i = 0; i < 4; i++) {
                        uint32_t z = y1[it][i];
                        if (it >= 1) z = hadd2(z, y2[it][i]);
                        if (it >= 2) z = hadd2(z, y3[it][i]);
                        v[2 * i] += bf_lo(z); v[2 * i + 1] += bf_hi(z);
                    }
                }
                if (it >= 2 || (it == 1 && wg)) {
#pragma unroll
                    for (int i = 0; i < 8; i++) v[i] = fmaf(g1024, ((i + 5) & 1) ? bf_hi(pq[it][(i + 5) >> 1]) : bf_lo(pq[it][(i + 5) >> 1]), v[i]);
                }
                if (it == 0 && ta == 31) v[7] = fmaf(g256, s0, v[7]);
                if (it == 0 && ta == 63) { v[6] = fmaf(g512, s0, v[6]); v[7] = fmaf(g512, s1, v[7]); }
                if (it == 1 && ta == 127) { v[4] = fmaf(g1024, s0, v[4]); v[5] = fmaf(g1024, s1, v[5]); v[6] = fmaf(g1024, s2, v[6]); v[7] = fmaf(g1024, s3, v[7]); }
                sts128(ay + 1024 * it, pack_bf16(v[0], v[1]), pack_bf16(v[2], v[3]), pack_bf16(v[4], v[5]), pack_bf16(v[6], v[7]));
            }
            fence_async_smem();
            __syncwarp();
            if (lane == 0) mbar_arrive(BAR(B_YST));
            CLK(9 + wg);
            if (warp == 0) GTM(39);
        }
        if (wg == 0) {
            float acc[64];
            mbar_wait(BAR(B_ODONE), 0);
            CLK(11 + wg);
            uint64_t da = mkdesc(sb + PQ_OFF, 16), db = mkdesc(sb + WO_OFF, 8192);
            int ks = 0;
#pragma unroll 1
            for (int ch = 0; ch < 5; ch++) {
                mbar_wait(BAR(B_WO + ch), 0);
                if (ch == 1) db = mkdesc(sb + WO2_OFF, WO2_HALF);
                wg_fence();
#pragma unroll 1
                for (int i = 0; i < (ch ? 7 : 4); i++, ks++) {
                    wgmma128(acc, da, db, ks);
                    db += 128;
                    da += (ks & 3) == 3 ? 512 - 6 : 2;
                }
                wg_commit();
            }
            wg_wait<0>();
            CLK(13 + wg);
            bar_sync(10, 128);
#pragma unroll
            for (int j = 0; j < 8; j++) {
                const int a = j * 8;
                stsm4(sb + PQ_OFF + (j >> 2) * 8192 + w4 * 2048 + frow + ((((j & 3) * 2 + (mi >> 1)) ^ rr) << 4), pack_bf16(acc[a], acc[a + 1]), pack_bf16(acc[a + 2], acc[a + 3]),
                      pack_bf16(acc[a + 4], acc[a + 5]), pack_bf16(acc[a + 6], acc[a + 7]));
            }
            fence_async_smem();
            bar_sync(10, 128);
            if (w4 == 0 && elect_one()) {
#pragma unroll 1
                for (int j = 0; j < 2; j++) tma2d_store(&mOut, 512 + (nt >> 1) * 128 + j * 64, (2 * mt + (nt & 1)) * 64, sb + PQ_OFF + j * 8192);
                bulk_commit();
                bulk_wait0_read();
            }
            CLK(15 + wg);
        }
    } else if (warp < 12) {
        asm volatile("setmaxnreg.inc.sync.aligned.u32 152;");
        const int aw = warp - 8, m = aw * 32 + lane;
        const int ch0 = nt * 64 + mt * 4;
        uint32_t prm[4][4];
        {
            const int idx = ch0 * 128 + m;
            const unsigned short* const q0 = reinterpret_cast<const unsigned short*>(p.A_re) + idx; const unsigned short* const q1 = reinterpret_cast<const unsigned short*>(p.A_im) + idx;
            const unsigned short* const q2 = reinterpret_cast<const unsigned short*>(p.B_re) + idx; const unsigned short* const q3 = reinterpret_cast<const unsigned short*>(p.B_im) + idx;
            const unsigned short* const q4 = reinterpret_cast<const unsigned short*>(p.C_re) + idx; const unsigned short* const q5 = reinterpret_cast<const unsigned short*>(p.C_im) + idx;
            const unsigned short* const q6 = reinterpret_cast<const unsigned short*>(p.log_dt) + ch0;
            unsigned short raw[4][7];
#pragma unroll
            for (int c = 0; c < 4; c++) {
                raw[c][0] = __ldg(q0 + c * 128); raw[c][1] = __ldg(q1 + c * 128); raw[c][2] = __ldg(q2 + c * 128); raw[c][3] = __ldg(q3 + c * 128);
                raw[c][4] = __ldg(q4 + c * 128); raw[c][5] = __ldg(q5 + c * 128); raw[c][6] = __ldg(q6 + c);
            }
#pragma unroll
            for (int c = 0; c < 4; c++) {
                prm[c][0] = raw[c][0] | ((uint32_t)raw[c][1] << 16); prm[c][1] = raw[c][2] | ((uint32_t)raw[c][3] << 16);
                prm[c][2] = raw[c][4] | ((uint32_t)raw[c][5] << 16); prm[c][3] = (uint32_t)raw[c][6] << 16;
            }
        }
#pragma unroll 1
        for (int c = 0; c < 4; c++) {
            const uint32_t pa = prm[0][0], pb_ = prm[0][1], pc = prm[0][2];
            const float dt = bf16_round(expf(__uint_as_float(prm[0][3])));
#pragma unroll
            for (int i = 0; i < 4; i++) { prm[0][i] = prm[1][i]; prm[1][i] = prm[2][i]; prm[2][i] = prm[3][i]; }
            if (c == UHOP_AT) {
                mbar_wait(BAR(B_UTILE), 0);
                transpose_inplace(sb + STG_OFF, aw, lane);
                if (lane == 0) mbar_arrive(BAR(B_SOUT));
                CLK(17);
            }
            if (c == 3) mbar_wait(BAR(B_S2FREE), 0);
            const float sg2 = (dt * bf_lo(pa)) * 1.4426950408889634f, wt = (dt * bf_hi(pa)) * 0.15915494309189535f;
            C2 cc; { C2 cq = {bf_lo(pc), -bf_hi(pc)}, bq = {dt * bf_lo(pb_), -dt * bf_hi(pb_)}; cc = cmul(cq, bq); }
            const uint32_t pb = sb + (c < 3 ? CH012_OFF + c * CH_BYTES : CH3_OFF) + m * 4;
            auto gen8 = [&](int row, C2 base, C2 r1, C2 r2, C2 r3) {
                const C2 x1 = cmul(base, r1), x2 = cmul(base, r2), x4 = cmul(base, r3);
                const C2 x3 = cmul(x1, r2), x5 = cmul(x1, r3), x6 = cmul(x2, r3), x7 = cmul(x3, r3);
                const uint32_t a = pb + row * PARK_PITCH;
                sts32(a, pack_bf16(base.r, base.i)); sts32(a + PARK_PITCH, pack_bf16(x1.r, x1.i));
                sts32(a + 2 * PARK_PITCH, pack_bf16(x2.r, x2.i)); sts32(a + 3 * PARK_PITCH, pack_bf16(x3.r, x3.i));
                sts32(a + 4 * PARK_PITCH, pack_bf16(x4.r, x4.i)); sts32(a + 5 * PARK_PITCH, pack_bf16(x5.r, x5.i));
                sts32(a + 6 * PARK_PITCH, pack_bf16(x6.r, x6.i)); sts32(a + 7 * PARK_PITCH, pack_bf16(x7.r, x7.i));
                return x7;
            };
            const C2 E1 = cexp_t(sg2, -wt, 1.f), E128 = cexp_t(sg2, -wt, 128.f), E8 = cexp_t(sg2, wt, 8.f);
            const C2 E2 = csq(E1), E4 = csq(E2), E16 = csq(E8), E32 = csq(E16), E256 = csq(E128), E512 = csq(E256);
            const C2 one = {1.f, 0.f};
            gen8(0, one, E8, E16, E32);
            gen8(8, csq(E32), E8, E16, E32);
            gen8(16, cc, E1, E2, E4);
            gen8(24, cmul(cc, E128), E1, E2, E4);
            gen8(32, cmul(cc, E256), E2, E4, E128);
            gen8(40, cmul(cc, E512), E4, E128, E256);
            const C2 x7 = gen8(48, cmul(cc, csq(E512)), E128, E256, E512);
            float v = fmaf(x7.r, E128.r, -(x7.i * E128.i));
#pragma unroll
            for (int o = 16; o > 0; o >>= 1) v += __shfl_xor_sync(0xffffffffu, v, o);
            if (lane == 0) sts32(sb + MISC_OFF + 64 + (c * 4 + aw) * 4, __float_as_uint(v));
        }
        bar_sync(12, 128);
        CLK(18);
        const int c = aw;
        const float dsk = __bfloat162float(p.Dskip[ch0 + c]);
        float g2048 = 0.f;
#pragma unroll
        for (int w = 0; w < 4; w++) g2048 += __uint_as_float(lds32(sb + MISC_OFF + 64 + (c * 4 + w) * 4));
        const uint32_t cb_ = sb + (c < 3 ? CH012_OFF + c * CH_BYTES : CH3_OFF);
        mbar_wait(BAR(B_T1), 0);
        CLK(19);
        {
            float G[5][4];
#pragma unroll
            for (int n = 0; n < 5; n++) { G[n][0] = G[n][1] = G[n][2] = G[n][3] = 0.f; }
            uint32_t pa = cb_ + ((mi & 1) * 8 + rr) * PARK_PITCH + (mi >> 1) * 16;
            uint32_t pbb = cb_ + (16 + rr) * PARK_PITCH + mi * 16;
            uint32_t fa[2][2][4], fb[2][5][4];
            ldsm4(pa, fa[0][0]); ldsm4(pa + 32, fa[0][1]);
#pragma unroll
            for (int n = 0; n < 5; n++) ldsm4(pbb + n * 8 * PARK_PITCH, fb[0][n]);
#pragma unroll 1
            for (int ks = 0; ks < 4; ks++) {
#pragma unroll
                for (int h = 0; h < 2; h++) {
                    pa += 64; pbb += 64;
                    ldsm4(pa, fa[h ^ 1][0]); ldsm4(pa + 32, fa[h ^ 1][1]);
#pragma unroll
                    for (int n = 0; n < 5; n++) ldsm4(pbb + n * 8 * PARK_PITCH, fb[h ^ 1][n]);
#pragma unroll
                    for (int n = 0; n < 5; n++) mma16816(G[n], fa[h][0][0], fa[h][0][1], fa[h][0][2], fa[h][0][3], fb[h][n][0], fb[h][n][1]);
#pragma unroll
                    for (int n = 0; n < 5; n++) mma16816(G[n], fa[h][1][0], fa[h][1][1], fa[h][1][2], fa[h][1][3], fb[h][n][2], fb[h][n][3]);
                }
            }
            __syncwarp();
            if (lane == 0) mbar_arrive(BAR(B_KM + c));
            if (aw == 0) CLK(34);
#pragma unroll
            for (int i = 0; i < 8; i++) if (i < 7 || lane < 6) sts128(cb_ + (i * 32 + lane) * 16, 0u, 0u, 0u, 0u);
            const float g256 = __shfl_sync(0xffffffffu, G[2][0], 0), g512 = __shfl_sync(0xffffffffu, G[3][0], 0), g1024 = __shfl_sync(0xffffffffu, G[4][0], 0);
            if (aw == 0) CLK(35);
            if (lane == 0) G[0][0] += dsk;
            if (lane == 31) { G[1][3] -= g256; G[2][3] -= g512; G[3][3] -= g1024; }
            __syncwarp();
            if (lane < 3) sts32(sb + MISC_OFF + 128 + c * 16 + lane * 4, __float_as_uint(bf16_round(lane == 0 ? g256 : (lane == 1 ? g512 : g1024))));
            if (lane < 2) sts16(cb_ + 1184 + 4 * 416 + 32 + lane * 210, bf16_bits(g2048));
#pragma unroll
            for (int n = 0; n < 5; n++) {
                const uint32_t base = n < 2 ? cb_ + 2 * (272 - 128 * n) - 4 * t - 16 * g
                                    : n == 2 ? cb_ + 1184 + 160 - 64 * (t >> 1) - 2 * (t & 1) - 4 * g
                                    : n == 3 ? cb_ + 1184 + 832 + 160 - 32 * t - 2 * g
                                             : cb_ + 1184 + 1664 + 160 + 416 * (g & 1) - 32 * t - 2 * (g >> 1);
                const int dg = n < 2 ? -2 : (n < 4 ? 416 : -16), dq = n < 2 ? -128 : (n == 2 ? -32 : (n == 3 ? -16 : -8)), cs = n < 2 ? 594 : 210;
#pragma unroll
                for (int i = 0; i < 4; i++) {
                    const uint32_t hv = bf16_bits(G[n][i]);
                    sts16(base + (i & 1) * dg + (i >> 1) * dq, hv); sts16(base + (i & 1) * dg + (i >> 1) * dq + cs, hv);
                }
            }
            __syncwarp();
            if (lane == 0) mbar_arrive(BAR(B_TAPS + c));
        }
        CLK(20);
        const uint32_t ub = sb + U_OFF + c * U_CH;
        {
            const uint32_t fl = cb_ + (g & 1) * 592 + (t - (g >> 1)) * 4 + 136 * 4;
            uint32_t P0[34], P1[34];
            {
                uint32_t F[34];
#pragma unroll
                for (int i = 0; i < 34; i++) F[i] = lds32(fl - 16 * (i - 1));
#pragma unroll
                for (int i = 0; i < 34; i++) {
                    P0[i] = i <= 32 ? F[i + 1] : 0u; P1[i] = F[i];
                    asm volatile("mov.b32 %0, %0;" : "+r"(P0[i])); asm volatile("mov.b32 %0, %0;" : "+r"(P1[i]));
                }
            }
            mbar_wait(BAR(B_UT), 0);
            const uint32_t ua = ub + U_PRE + ((mi & 1) * 8 + rr) * 272 + (mi >> 1) * 16;
            const uint32_t yb = cb_ + Y0_REL + g * 272 + t * 4;
#pragma unroll 1
            for (int gm = 0; gm < 2; gm++) {
                float acc[8][4];
#pragma unroll
                for (int i = 0; i < 8; i++) { acc[i][0] = acc[i][1] = acc[i][2] = acc[i][3] = 0.f; }
                uint32_t a[3][4];
                const uint32_t ub0 = ua + gm * 128, ub1 = ua + gm * 144;
                auto addr = [&](int kp) { const int m0 = -2 * kp, f0 = m0 >> 4, f1 = (m0 + 8) >> 4; return (f1 != f0 ? ub1 : ub0) + (uint32_t)((m0 + f0) * 16); };
                ldsm4(addr(-3), a[0]); ldsm4(addr(-2), a[1]);
#pragma unroll
                for (int kp = -3; kp <= 16; kp++) {
                    if (kp + 2 <= 16) ldsm4(addr(kp + 2), a[(kp + 5) % 3]);
                    const uint32_t* aa = a[(kp + 3) % 3];
#pragma unroll
                    for (int d = 0; d < 8; d++) {
                        const int i = d + 2 * kp;
                        if (i >= 0 && i <= 33) mma16816(acc[d], aa[0], aa[1], aa[2], aa[3], P0[i], P1[i]);
                    }
                }
#pragma unroll
                for (int d = 0; d < 8; d++) {
                    sts32(yb + (8 * gm + d) * 16, pack_bf16(acc[d][0], acc[d][1]));
                    sts32(yb + (8 * gm + d) * 16 + 8 * 272, pack_bf16(acc[d][2], acc[d][3]));
                }
            }
            bar_arrive(6 + c, 96);
            CLK(21);
        }
        {
            mbar_wait(BAR(B_KVOK), 0);
            CLK(22);
            const float* kv = g_KV[lds32(sb + MISC_OFF) & 1];
            uint32_t kb1[8][4], zb1[8][2];
            {
                const float4* kp = reinterpret_cast<const float4*>(kv + aw * 2048) + lane;
                const float4* zp = reinterpret_cast<const float4*>(kv + 8192 + aw * 128) + t;
#pragma unroll
                for (int hh = 0; hh < 8; hh++) {
                    const float4 x = __ldcg(kp + hh * 64), y = __ldcg(kp + hh * 64 + 32), z = __ldcg(zp + hh * 4);
                    kb1[hh][0] = pack_bf16(x.x, x.y); kb1[hh][1] = pack_bf16(x.z, x.w); kb1[hh][2] = pack_bf16(y.x, y.y); kb1[hh][3] = pack_bf16(y.z, y.w);
                    zb1[hh][0] = pack_bf16(z.x, z.y); zb1[hh][1] = pack_bf16(z.z, z.w);
                }
            }
            mbar_wait(BAR(B_CONV), 0);
#pragma unroll
            for (int jb = 0; jb < 2; jb++) {
                const int box = aw * 2 + jb;
                const uint32_t (*kb0)[4] = kb1 + jb * 4;
                const uint32_t (*zb)[2] = zb1 + jb * 4;
                mbar_wait(BAR(B_PQ + box), 0);
                uint32_t bx = sb + PQ_OFF + box * 8192 + ((mi & 1) * 8 + rr) * 128;
                uint32_t an[4][4];
#pragma unroll
                for (int hh = 0; hh < 4; hh++) ldsm4(bx + (((hh * 2 + (mi >> 1)) ^ rr) << 4), an[hh]);
#pragma unroll 1
                for (int mm = 0; mm < 4; mm++, bx += 2048) {
                    uint32_t a[4][4];
                    float n0[4][4], n1[4][4], dn[4][4];
#pragma unroll
                    for (int hh = 0; hh < 4; hh++) {
                        a[hh][0] = an[hh][0]; a[hh][1] = an[hh][1]; a[hh][2] = an[hh][2]; a[hh][3] = an[hh][3];
                        if (mm < 3) ldsm4(bx + 2048 + (((hh * 2 + (mi >> 1)) ^ rr) << 4), an[hh]);
                    }
#pragma unroll
                    for (int hh = 0; hh < 4; hh++) mma16816c(dn[hh], a[hh], zb[hh][0], zb[hh][1], 1e-6f);
#pragma unroll
                    for (int hh = 0; hh < 4; hh++) {
                        mma16816c(n0[hh], a[hh], kb0[hh][0], kb0[hh][1], 0.f);
                        mma16816c(n1[hh], a[hh], kb0[hh][2], kb0[hh][3], 0.f);
                    }
#pragma unroll
                    for (int hh = 0; hh < 4; hh++) {
                        const float i0 = rcpf(dn[hh][0]), i1 = rcpf(dn[hh][2]);
                        stsm4(bx + (((hh * 2 + (mi >> 1)) ^ rr) << 4), pack_bf16(n0[hh][0] * i0, n0[hh][1] * i0), pack_bf16(n0[hh][2] * i1, n0[hh][3] * i1),
                              pack_bf16(n1[hh][0] * i0, n1[hh][1] * i0), pack_bf16(n1[hh][2] * i1, n1[hh][3] * i1));
                    }
                }
            }
            fence_async_smem();
            __syncwarp();
            if (lane == 0) mbar_arrive(BAR(B_ODONE));
            CLK(23);
        }
        mbar_wait(BAR(B_YT), 0);
        CLK(24);
        transpose_inplace(sb + STG_OFF, aw, lane);
        if (aw == 0) CLK(41);
        if (lane == 0) mbar_arrive(BAR(B_YOUT));
    } else {
      asm volatile("setmaxnreg.dec.sync.aligned.u32 40;");
      if (warp == 12) {
        if (elect_one()) {
            int s = 0, ph = 0;
#pragma unroll 1
            for (int kb = 3; kb < 8; kb++) {
                mbar_wait(BAR(B_EMPTY1 + s), ph);
                const uint32_t full = BAR(B_FULL1 + s), sa = sb + s * STAGE1;
                mbar_expect_tx(full, STAGE1);
                tma2d(sa, &mX, kb * 64, mt * 128, full);
#pragma unroll 1
                for (int j = 0; j < 3; j++) tma2d(sa + XB1 + j * WB1, &mW, j * 512 + nt * 64, kb * 64, full);
                if (++s == 3) { s = 0; ph ^= 1; }
            }
            CLKL(31);
            mbar_wait(BAR(B_T1), 0);
            mbar_expect_tx(BAR(B_WO), 16384);
#pragma unroll 1
            for (int j = 0; j < 2; j++) tma2d(sb + WO_OFF + j * 8192, &mWO, (nt >> 1) * 128 + j * 64, 0, BAR(B_WO));
            mbar_wait(BAR(B_YST), 0);
#pragma unroll 1
            for (int ch = 0; ch < 4; ch++) {
                if (ch == 1) mbar_wait(BAR(B_YRDY), 0);
                mbar_expect_tx(BAR(B_WO + 1 + ch), 2 * 14336);
#pragma unroll 1
                for (int j = 0; j < 2; j++)
                    tma2d(sb + WO2_OFF + j * WO2_HALF + ch * 14336, &mWO2, (nt >> 1) * 128 + j * 64, 64 + ch * 112, BAR(B_WO + 1 + ch));
            }
        }
      } else if (warp == 13) {
        unsigned int epoch;
        asm volatile("ld.relaxed.gpu.global.u32 %0, [%1];" : "=r"(epoch) : "l"(g_cnt) : "memory");
        epoch >>= 7;
        if (lane == 0) { sts32(sb + MISC_OFF, epoch); mbar_arrive(BAR(B_EPOCH)); }
        {
            float* other = g_KV[(epoch + 1) & 1] + blockIdx.x * 68;
            other[lane] = 0.f; other[lane + 32] = 0.f; if (lane < 4) other[lane + 64] = 0.f;
        }
        const bool leader = elect_one();
        if (leader) {
            {
                const int kx = nt, kw = mt & 7;
                const int first = kx < kw ? kx : kw;
#pragma unroll 1
                for (int ps = 0; ps < 2; ps++) {
                    const bool isx = (ps == 0) == (kx <= kw);
                    const int kb = isx ? kx : kw;
                    if (kb >= 3) {
                        while ((int)(clock() - t0) < PF_T0 + PF_DT * (kb - 3)) { }
                        if (isx) tma_prefetch2d(&mX, kb * 64, mt * 128);
                        else { tma_prefetch2d(&mW, (mt >> 3) * 512 + nt * 64, kb * 64); if (mt >= 8) tma_prefetch2d(&mW, 1024 + nt * 64, kb * 64); }
                    }
                }
                (void)first;
            }
            mbar_wait(BAR(B_GO), 0);
            mbar_expect_tx(BAR(B_UTILE), 16384);
            tma2d(sb + STG_OFF, &mU, nt * 64, mt * 128, BAR(B_UTILE));
            mbar_wait(BAR(B_UTILE), 0);
            asm volatile("cp.async.bulk.prefetch.L2.global [%0], %1;" :: "l"(reinterpret_cast<const unsigned char*>(p.wo) + blockIdx.x * 4096), "r"(4096) : "memory");
            mbar_wait(BAR(B_SOUT), 0);
#pragma unroll 1
            for (int j = 0; j < 2; j++) tma3d_store(&mUT, j * 64, mt, nt * 64, sb + STG_OFF + j * 8192);
            bulk_commit();
            bulk_wait0();
        }
        __syncwarp();
#pragma unroll 1
        for (int c = 0; c < 4; c++) { sts128(sb + U_OFF + c * U_CH + lane * 16, 0u, 0u, 0u, 0u); if (lane < 6) sts128(sb + U_OFF + c * U_CH + 512 + lane * 16, 0u, 0u, 0u, 0u); }
        __syncwarp();
        if (leader) {
            group_barrier(&g_cnt[32 * (1 + nt)], (epoch + 1) * 16);
            mbar_expect_tx(BAR(B_UT), 4 * 4352);
#pragma unroll 1
            for (int c = 0; c < 4; c++) bulk_g2s(sb + U_OFF + c * U_CH + U_PRE, g_UT + (size_t)(nt * 64 + mt * 4 + c) * 2176, 4352, BAR(B_UT));
            CLKL(25);
            mbar_wait(BAR(B_QT), 0);
#pragma unroll 1
            for (int j = 0; j < 2; j++) tma2d_store(&mQ, nt * 64, mt * 128 + j * 64, sb + QT_OFF + j * 8192);
            bulk_commit();
            bulk_wait0();
            CLKL(26);
            group_barrier(&g_cnt[32 * (17 + mt)], (epoch + 1) * 8);
            mbar_wait(BAR(B_KV), 0);
            CLKL(27);
#pragma unroll 1
            for (int j = 0; j < 8; j++) {
                mbar_expect_tx(BAR(B_PQ + j), 8192);
                tma2d(sb + PQ_OFF + j * 8192, &mQ, j * 64, (2 * mt + (nt & 1)) * 64, BAR(B_PQ + j));
            }
            mbar_wait(BAR(B_YST), 0);
#pragma unroll 1
            for (int c = 0; c < 4; c++)
                bulk_s2g(g_YT + (size_t)(nt * 64 + mt * 4 + c) * L_, sb + (c < 3 ? CH012_OFF + c * CH_BYTES : CH3_OFF) + (c == 0 ? 0 : X1E + EO), 4096);
            bulk_commit();
            bulk_wait0_read();
            mbar_arrive(BAR(B_YRDY));
            bulk_wait0();
            group_barrier(&g_cnt[32 * (9 + nt)], (epoch + 1) * 16);
            CLKL(28);
            mbar_expect_tx(BAR(B_YT), 16384);
#pragma unroll 1
            for (int j = 0; j < 2; j++) tma2d(sb + STG_OFF + j * 8192, &mYT, mt * 128 + j * 64, nt * 64, BAR(B_YT));
            mbar_wait(BAR(B_YOUT), 0);
            CLKL(42);
#pragma unroll 1
            for (int j = 0; j < 2; j++) tma2d_store(&mOut, nt * 64, mt * 128 + j * 64, sb + STG_OFF + j * 8192);
            bulk_commit();
            CLKL(43);
            bulk_wait0_read();
            CLKL(29);
        }
      } else if (warp == 14) {
        if (elect_one()) {
            mbar_wait(BAR(B_EPOCH), 0);
            const uint32_t epoch = lds32(sb + MISC_OFF);
            mbar_wait(BAR(B_KV), 0);
            CLKL(32);
            float* kv = g_KV[epoch & 1];
            bulk_red_f32(kv + nt * 1024, sb + KVS_OFF, 4096);
            bulk_red_f32(kv + 8192 + nt * 64, sb + KVS_OFF + 4096, 256);
            bulk_commit();
            bulk_wait0();
            group_barrier(&g_cnt[0], (epoch + 1) * 128);
            mbar_arrive(BAR(B_KVOK));
            CLKL(33);
        }
      }
    }
}

typedef CUresult (*PFN_encodeTiled)(CUtensorMap*, CUtensorMapDataType, cuuint32_t, void*, const cuuint64_t*, const cuuint64_t*, const cuuint32_t*,
                                    const cuuint32_t*, CUtensorMapInterleave, CUtensorMapSwizzle, CUtensorMapL2promotion, CUtensorMapFloatOOBfill);

struct HostState {
    bool init = false;
    PFN_encodeTiled enc = nullptr;
    void *ut = nullptr, *yt = nullptr, *q = nullptr;
};

void make_map(PFN_encodeTiled enc, CUtensorMap* m, const void* base, int rank, const cuuint64_t* dims, const cuuint64_t* strides, const cuuint32_t* box) {
    const cuuint32_t es[3] = {1, 1, 1};
    enc(m, CU_TENSOR_MAP_DATA_TYPE_BFLOAT16, (cuuint32_t)rank, const_cast<void*>(base), dims, strides, box, es, CU_TENSOR_MAP_INTERLEAVE_NONE,
        CU_TENSOR_MAP_SWIZZLE_128B, CU_TENSOR_MAP_L2_PROMOTION_L2_128B, CU_TENSOR_MAP_FLOAT_OOB_FILL_NONE);
}
void make_map2(PFN_encodeTiled enc, CUtensorMap* m, const void* base, uint64_t inner, uint64_t outer, uint32_t bi, uint32_t bo) {
    const cuuint64_t dims[2] = {inner, outer}; const cuuint64_t strides[1] = {inner * 2}; const cuuint32_t box[2] = {bi, bo};
    make_map(enc, m, base, 2, dims, strides, box);
}

}

extern "C" void kernel_launch(void* const* d_in, const int* in_sizes, int n_in, void* d_out, int out_size) {
    (void)in_sizes; (void)n_in; (void)out_size;
    static HostState hs;
    if (!hs.init) {
        void* fn = nullptr; cudaDriverEntryPointQueryResult qr;
        cudaGetDriverEntryPoint("cuTensorMapEncodeTiled", &fn, cudaEnableDefault, &qr);
        hs.enc = (PFN_encodeTiled)fn;
        cudaGetSymbolAddress(&hs.ut, g_UT); cudaGetSymbolAddress(&hs.yt, g_YT); cudaGetSymbolAddress(&hs.q, g_Q);
        cudaFuncSetAttribute(fused_kernel, cudaFuncAttributeMaxDynamicSharedMemorySize, SMEM_BYTES);
        hs.init = true;
    }
    CUtensorMap mX, mW, mU, mUT, mQ, mWO, mWO2, mYT, mOut;
    make_map2(hs.enc, &mX, d_in[9], 512, 2048, 64, 128);
    make_map2(hs.enc, &mW, d_in[10], 1536, 512, 64, 64);
    make_map2(hs.enc, &mU, d_in[0], 512, 2048, 64, 128);
    {
        const cuuint64_t dims[3] = {128, 16, 512}; const cuuint64_t strides[2] = {272, 4352}; const cuuint32_t box[3] = {64, 1, 64};
        make_map(hs.enc, &mUT, hs.ut, 3, dims, strides, box);
    }
    make_map2(hs.enc, &mQ, hs.q, 512, 2048, 64, 64);
    make_map2(hs.enc, &mWO, d_in[11], 512, 512, 64, 64);
    make_map2(hs.enc, &mWO2, d_in[11], 512, 512, 64, 112);
    make_map2(hs.enc, &mYT, hs.yt, 2048, 512, 64, 64);
    make_map2(hs.enc, &mOut, d_out, 1024, 2048, 64, 64);
    Params p;
    p.A_re = (const __nv_bfloat16*)d_in[1]; p.A_im = (const __nv_bfloat16*)d_in[2];
    p.B_re = (const __nv_bfloat16*)d_in[3]; p.B_im = (const __nv_bfloat16*)d_in[4];
    p.C_re = (const __nv_bfloat16*)d_in[5]; p.C_im = (const __nv_bfloat16*)d_in[6];
    p.log_dt = (const __nv_bfloat16*)d_in[7]; p.Dskip = (const __nv_bfloat16*)d_in[8];
    p.wo = (const __nv_bfloat16*)d_in[11];
    p.zero = 0;
    fused_kernel<<<128, NTHREADS, SMEM_BYTES>>>(mX, mW, mU, mUT, mQ, mWO, mWO2, mYT, mOut, p);
}
```
